```python
import torch

def _softmax(x, axis=-1):
    return torch.softmax(x, dim=axis)

def _gelu(x):
    return torch.nn.functional.gelu(x, approximate='tanh')

def _silu(x):
    return torch.nn.functional.silu(x)

def _sigmoid(x):
    return torch.sigmoid(x)

def _layernorm(x, axis=-1, eps=1e-05):
    m = x.mean(dim=axis, keepdim=True)
    v = x.var(dim=axis, keepdim=True, unbiased=False)
    return (x - m) / torch.sqrt(v + eps)

def _scatter_add(tgt, idx, src, axis=0):
    return tgt.clone().index_add_(axis, idx, src)

def _segment_sum(src, seg, n):
    out = torch.zeros((n,) + src.shape[1:], dtype=src.dtype)
    return out.index_add_(0, seg, src)

def _pad(x, pw):
    flat = tuple((v for pair in reversed(pw) for v in pair))
    return torch.nn.functional.pad(x, flat)
kernel_name = 'adaLN_cond__sliding_block_cached__dense_activation_relu__prompt'

def setup_inputs():

    _w = lambda a: (lambda t: t.to(torch.bfloat16) if t.is_floating_point() else t)(torch.as_tensor(a))

    def _A_setup():
        B, Sq, D = (1, 2048, 448)
        Hq, Hkv, Sk, Dh = (16, 8, 2048, 256)
        assert Hq % Hkv == 0, (Hq, Hkv)
        return {'x': _w((lambda *s: torch.randn(*s, dtype=torch.bfloat16) * 0.05)(B, Sq, D)), 'k_cache': _w((lambda *s: torch.randn(*s, dtype=torch.bfloat16) * 3.2)(B, Hkv, Sk, Dh)), 'v_cache': _w((lambda *s: torch.randn(*s, dtype=torch.bfloat16) * 0.4)(B, Hkv, Sk, Dh)), 'wq': _w((lambda *s: torch.randn(*s, dtype=torch.bfloat16) * 3.2)(D, Hq * Dh) * D ** (-0.5)), 'wo': _w((lambda *s: torch.randn(*s, dtype=torch.bfloat16) * 0.4)(Hq * Dh, D) * (Hq * Dh) ** (-0.5))}
    _A_in = _A_setup()

    def _B_setup():
        B, S, D, Dff = (1, 2048, 448, 1792)
        return {'x': _w((lambda *s: torch.randn(*s, dtype=torch.bfloat16) * 0.05)(B, S, D)), 'w1': _w((lambda *s: torch.randn(*s, dtype=torch.bfloat16) * 0.05)(D, Dff)), 'w2': _w((lambda *s: torch.randn(*s, dtype=torch.bfloat16) * 0.05)(Dff, D))}
    _B_in = _B_setup()
    return {'A_x': _A_in['x'], 'A_k_cache': _A_in['k_cache'], 'A_v_cache': _A_in['v_cache'], 'A_wq': _A_in['wq'], 'A_wo': _A_in['wo'], 'B_x': _B_in['x'], 'B_w1': _B_in['w1'], 'B_w2': _B_in['w2'], 'c': _w((lambda *s: torch.randn(*s, dtype=torch.bfloat16) * 0.1)(1, 448) * 8.0), 'w_mod': _w((lambda *s: torch.randn(*s, dtype=torch.bfloat16) * 0.1)(448, 6 * 448) * 448 ** (-0.5) * 8.0)}

def reference(A_x, A_k_cache, A_v_cache, A_wq, A_wo, B_x, B_w1, B_w2, c, w_mod):

    def _A_ref(x, k_cache, v_cache, wq, wo):
        B, Sq, D = x.shape
        Hq, Dh = (16, 256)
        Hkv, Sk = (k_cache.shape[1], k_cache.shape[2])
        W = min(4096, max(256, Sk // 4))
        rep = Hq // Hkv
        q = (lambda x, *d: x.permute(*d))((x @ wq).reshape(B, Sq, Hq, Dh), 0, 2, 1, 3)
        k = (lambda x, n, axis: torch.repeat_interleave(x, n, dim=axis))(k_cache[:, :, Sk - W:, :], rep, axis=1)
        v = (lambda x, n, axis: torch.repeat_interleave(x, n, dim=axis))(v_cache[:, :, Sk - W:, :], rep, axis=1)
        scores = torch.einsum('bhqd,bhkd->bhqk', q, k) * Dh ** (-0.5)
        p = _softmax(scores, axis=-1)
        o = torch.einsum('bhqk,bhkd->bhqd', p, v)
        return (lambda x, *d: x.permute(*d))(o, 0, 2, 1, 3).reshape(B, Sq, Hq * Dh) @ wo

    def _B_ref(x, w1, w2):
        h = torch.einsum('bsd,df->bsf', x, w1)
        zero = torch.zeros_like(h)
        h = torch.maximum(h, zero)
        return torch.einsum('bsf,fd->bsd', h, w2)
    x = A_x
    mod = (_silu(c) @ w_mod).reshape(c.shape[0], 6, 1, -1)
    sa, ca, ga, sb, cb, gb = (mod[:, 0].clone(), mod[:, 1].clone(), mod[:, 2].clone(), mod[:, 3].clone(), mod[:, 4].clone(), mod[:, 5].clone())
    h = _layernorm(x, axis=-1) * (1 + ca) + sa
    x = x + ga * _A_ref(h, A_k_cache, A_v_cache, A_wq, A_wo)
    h = _layernorm(x, axis=-1) * (1 + cb) + sb
    x = x + gb * _B_ref(h, B_w1, B_w2)
    return x
```

```cpp
#include <cuda_runtime.h>
#include <cuda_bf16.h>
#include <cuda.h>
#include <stdint.h>

constexpr int SEQ = 2048, DM = 448, HKV = 8, SKV = 2048, DH = 256, WIN = 512, DFF = 1792;

__device__ __align__(1024) float          g_mod[6 * DM];
__device__ __align__(1024) __nv_bfloat16  g_h[SEQ * DM];
__device__ __align__(1024) __nv_bfloat16  g_oA[HKV * SEQ * DH];
__device__ __align__(1024) float          g_acc1[SEQ * DM];
__device__ __align__(1024) float          g_acc2[SEQ * DM];
__device__ __align__(1024) __nv_bfloat16  g_x1[SEQ * DM];
__device__ __align__(1024) __nv_bfloat16  g_h2[SEQ * DM];

__device__ __forceinline__ uint32_t smem_u32(const void* p) { return (uint32_t)__cvta_generic_to_shared(p); }
__device__ __forceinline__ void mbar_init(uint32_t bar, uint32_t cnt) {
  asm volatile("mbarrier.init.shared::cta.b64 [%0], %1;" ::"r"(bar), "r"(cnt));
}
__device__ __forceinline__ void mbar_expect_tx(uint32_t bar, uint32_t bytes) {
  asm volatile("mbarrier.arrive.expect_tx.shared::cta.b64 _, [%0], %1;" ::"r"(bar), "r"(bytes) : "memory");
}
__device__ __forceinline__ void mbar_arrive(uint32_t bar) {
  asm volatile("mbarrier.arrive.shared::cta.b64 _, [%0];" ::"r"(bar) : "memory");
}
__device__ __forceinline__ void mbar_arrive_remote(uint32_t bar, uint32_t cta) {
  asm volatile("{\n.reg .b32 ra;\nmapa.shared::cluster.u32 ra, %0, %1;\n"
               "mbarrier.arrive.release.cluster.shared::cluster.b64 _, [ra];\n}\n" ::"r"(bar), "r"(cta) : "memory");
}
__device__ __forceinline__ void mbar_wait(uint32_t bar, uint32_t parity) {
  asm volatile("{\n.reg .pred p;\nLAB_WAIT:\n"
               "mbarrier.try_wait.parity.shared::cta.b64 p, [%0], %1, 0x989680;\n"
               "@p bra LAB_DONE;\nbra LAB_WAIT;\nLAB_DONE:\n}\n" ::"r"(bar), "r"(parity) : "memory");
}
__device__ __forceinline__ void mbar_wait_cluster(uint32_t bar, uint32_t parity) {
  asm volatile("{\n.reg .pred p;\nLAB_WAIT:\n"
               "mbarrier.try_wait.parity.acquire.cluster.shared::cta.b64 p, [%0], %1, 0x989680;\n"
               "@p bra LAB_DONE;\nbra LAB_WAIT;\nLAB_DONE:\n}\n" ::"r"(bar), "r"(parity) : "memory");
}
__device__ __forceinline__ void tma_load(uint32_t dst, const CUtensorMap* m, int c0, int c1, uint32_t bar) {
  asm volatile("cp.async.bulk.tensor.2d.shared::cluster.global.mbarrier::complete_tx::bytes [%0], [%1, {%3, %4}], [%2];"
               ::"r"(dst), "l"(m), "r"(bar), "r"(c0), "r"(c1) : "memory");
}
__device__ __forceinline__ void tma_load_mc(uint32_t dst, const CUtensorMap* m, int c0, int c1, uint32_t bar, uint16_t mask) {
  asm volatile("cp.async.bulk.tensor.2d.shared::cluster.global.mbarrier::complete_tx::bytes.multicast::cluster [%0], [%1, {%3, %4}], [%2], %5;"
               ::"r"(dst), "l"(m), "r"(bar), "r"(c0), "r"(c1), "h"(mask) : "memory");
}
__device__ __forceinline__ void cluster_sync_all() {
  asm volatile("barrier.cluster.arrive.release.aligned;\nbarrier.cluster.wait.acquire.aligned;\n" ::: "memory");
}
__device__ __forceinline__ uint32_t cluster_rank() { uint32_t r; asm volatile("mov.u32 %0, %%cluster_ctarank;" : "=r"(r)); return r; }
__device__ __forceinline__ void wg_fence() { asm volatile("wgmma.fence.sync.aligned;" ::: "memory"); }
__device__ __forceinline__ void wg_commit() { asm volatile("wgmma.commit_group.sync.aligned;" ::: "memory"); }
template <int N> __device__ __forceinline__ void wg_wait() { asm volatile("wgmma.wait_group.sync.aligned %0;" ::"n"(N) : "memory"); }
__device__ __forceinline__ void bar_sync(int id, int n) { asm volatile("bar.sync %0, %1;" ::"r"(id), "r"(n) : "memory"); }
__device__ __forceinline__ void fence_async() { asm volatile("fence.proxy.async;" ::: "memory"); }
__device__ __forceinline__ uint64_t mk_desc(uint32_t saddr, uint32_t lbo, uint32_t sbo) {
  return (uint64_t)((saddr & 0x3FFFF) >> 4) | ((uint64_t)(lbo >> 4) << 16) | ((uint64_t)(sbo >> 4) << 32) | (1ull << 62);
}
__device__ __forceinline__ uint32_t pack_bf16(float lo, float hi) {
  uint32_t r; asm("cvt.rn.bf16x2.f32 %0, %1, %2;" : "=r"(r) : "f"(hi), "f"(lo)); return r;
}
__device__ __forceinline__ float bf_lo(uint32_t v) { return __uint_as_float(v << 16); }
__device__ __forceinline__ float bf_hi(uint32_t v) { return __uint_as_float(v & 0xFFFF0000u); }
__device__ __forceinline__ float rbf(float x) { return __bfloat162float(__float2bfloat16_rn(x)); }
__device__ __forceinline__ float ex2(float x) { float r; asm("ex2.approx.ftz.f32 %0, %1;" : "=f"(r) : "f"(x)); return r; }
__device__ __forceinline__ void red_add_v2(float* p, float a, float b) {
  asm volatile("red.global.add.v2.f32 [%0], {%1, %2};" ::"l"(p), "f"(a), "f"(b) : "memory");
}
__device__ __forceinline__ void pdl_wait() { asm volatile("griddepcontrol.wait;" ::: "memory"); }
__device__ __forceinline__ void pdl_launch() { asm volatile("griddepcontrol.launch_dependents;" ::: "memory"); }

__device__ __forceinline__ void wgmma_m64n256k16_ss_tb(float (&d)[128], uint64_t da, uint64_t db, int sc) {
  asm volatile("{\n.reg .pred p;\nsetp.ne.b32 p, %130, 0;\n"
    "wgmma.mma_async.sync.aligned.m64n256k16.f32.bf16.bf16 {%0, %1, %2, %3, %4, %5, %6, %7, %8, %9, %10, %11, %12, %13, %14, %15, %16, %17, %18, %19, %20, %21, %22, %23, %24, %25, %26, %27, %28, %29, %30, %31, %32, %33, %34, %35, %36, %37, %38, %39, %40, %41, %42, %43, %44, %45, %46, %47, %48, %49, %50, %51, %52, %53, %54, %55, %56, %57, %58, %59, %60, %61, %62, %63, %64, %65, %66, %67, %68, %69, %70, %71, %72, %73, %74, %75, %76, %77, %78, %79, %80, %81, %82, %83, %84, %85, %86, %87, %88, %89, %90, %91, %92, %93, %94, %95, %96, %97, %98, %99, %100, %101, %102, %103, %104, %105, %106, %107, %108, %109, %110, %111, %112, %113, %114, %115, %116, %117, %118, %119, %120, %121, %122, %123, %124, %125, %126, %127}, %128, %129, p, 1, 1, 0, 1;\n}\n"
    : "+f"(d[0]), "+f"(d[1]), "+f"(d[2]), "+f"(d[3]), "+f"(d[4]), "+f"(d[5]), "+f"(d[6]), "+f"(d[7]), "+f"(d[8]), "+f"(d[9]), "+f"(d[10]), "+f"(d[11]), "+f"(d[12]), "+f"(d[13]), "+f"(d[14]), "+f"(d[15]), "+f"(d[16]), "+f"(d[17]), "+f"(d[18]), "+f"(d[19]), "+f"(d[20]), "+f"(d[21]), "+f"(d[22]), "+f"(d[23]), "+f"(d[24]), "+f"(d[25]), "+f"(d[26]), "+f"(d[27]), "+f"(d[28]), "+f"(d[29]), "+f"(d[30]), "+f"(d[31]), "+f"(d[32]), "+f"(d[33]), "+f"(d[34]), "+f"(d[35]), "+f"(d[36]), "+f"(d[37]), "+f"(d[38]), "+f"(d[39]), "+f"(d[40]), "+f"(d[41]), "+f"(d[42]), "+f"(d[43]), "+f"(d[44]), "+f"(d[45]), "+f"(d[46]), "+f"(d[47]), "+f"(d[48]), "+f"(d[49]), "+f"(d[50]), "+f"(d[51]), "+f"(d[52]), "+f"(d[53]), "+f"(d[54]), "+f"(d[55]), "+f"(d[56]), "+f"(d[57]), "+f"(d[58]), "+f"(d[59]), "+f"(d[60]), "+f"(d[61]), "+f"(d[62]), "+f"(d[63]), "+f"(d[64]), "+f"(d[65]), "+f"(d[66]), "+f"(d[67]), "+f"(d[68]), "+f"(d[69]), "+f"(d[70]), "+f"(d[71]), "+f"(d[72]), "+f"(d[73]), "+f"(d[74]), "+f"(d[75]), "+f"(d[76]), "+f"(d[77]), "+f"(d[78]), "+f"(d[79]), "+f"(d[80]), "+f"(d[81]), "+f"(d[82]), "+f"(d[83]), "+f"(d[84]), "+f"(d[85]), "+f"(d[86]), "+f"(d[87]), "+f"(d[88]), "+f"(d[89]), "+f"(d[90]), "+f"(d[91]), "+f"(d[92]), "+f"(d[93]), "+f"(d[94]), "+f"(d[95]), "+f"(d[96]), "+f"(d[97]), "+f"(d[98]), "+f"(d[99]), "+f"(d[100]), "+f"(d[101]), "+f"(d[102]), "+f"(d[103]), "+f"(d[104]), "+f"(d[105]), "+f"(d[106]), "+f"(d[107]), "+f"(d[108]), "+f"(d[109]), "+f"(d[110]), "+f"(d[111]), "+f"(d[112]), "+f"(d[113]), "+f"(d[114]), "+f"(d[115]), "+f"(d[116]), "+f"(d[117]), "+f"(d[118]), "+f"(d[119]), "+f"(d[120]), "+f"(d[121]), "+f"(d[122]), "+f"(d[123]), "+f"(d[124]), "+f"(d[125]), "+f"(d[126]), "+f"(d[127])
    : "l"(da), "l"(db), "r"(sc));
}
__device__ __forceinline__ void wgmma_m64n128k16_ss(float (&d)[64], uint64_t da, uint64_t db, int sc) {
  asm volatile("{\n.reg .pred p;\nsetp.ne.b32 p, %66, 0;\n"
    "wgmma.mma_async.sync.aligned.m64n128k16.f32.bf16.bf16 {%0, %1, %2, %3, %4, %5, %6, %7, %8, %9, %10, %11, %12, %13, %14, %15, %16, %17, %18, %19, %20, %21, %22, %23, %24, %25, %26, %27, %28, %29, %30, %31, %32, %33, %34, %35, %36, %37, %38, %39, %40, %41, %42, %43, %44, %45, %46, %47, %48, %49, %50, %51, %52, %53, %54, %55, %56, %57, %58, %59, %60, %61, %62, %63}, %64, %65, p, 1, 1, 0, 0;\n}\n"
    : "+f"(d[0]), "+f"(d[1]), "+f"(d[2]), "+f"(d[3]), "+f"(d[4]), "+f"(d[5]), "+f"(d[6]), "+f"(d[7]), "+f"(d[8]), "+f"(d[9]), "+f"(d[10]), "+f"(d[11]), "+f"(d[12]), "+f"(d[13]), "+f"(d[14]), "+f"(d[15]), "+f"(d[16]), "+f"(d[17]), "+f"(d[18]), "+f"(d[19]), "+f"(d[20]), "+f"(d[21]), "+f"(d[22]), "+f"(d[23]), "+f"(d[24]), "+f"(d[25]), "+f"(d[26]), "+f"(d[27]), "+f"(d[28]), "+f"(d[29]), "+f"(d[30]), "+f"(d[31]), "+f"(d[32]), "+f"(d[33]), "+f"(d[34]), "+f"(d[35]), "+f"(d[36]), "+f"(d[37]), "+f"(d[38]), "+f"(d[39]), "+f"(d[40]), "+f"(d[41]), "+f"(d[42]), "+f"(d[43]), "+f"(d[44]), "+f"(d[45]), "+f"(d[46]), "+f"(d[47]), "+f"(d[48]), "+f"(d[49]), "+f"(d[50]), "+f"(d[51]), "+f"(d[52]), "+f"(d[53]), "+f"(d[54]), "+f"(d[55]), "+f"(d[56]), "+f"(d[57]), "+f"(d[58]), "+f"(d[59]), "+f"(d[60]), "+f"(d[61]), "+f"(d[62]), "+f"(d[63])
    : "l"(da), "l"(db), "r"(sc));
}
__device__ __forceinline__ void wgmma_m64n256k16_rs_tb(float (&d)[128], uint32_t a0, uint32_t a1, uint32_t a2, uint32_t a3, uint64_t db, int sc) {
  asm volatile("{\n.reg .pred p;\nsetp.ne.b32 p, %133, 0;\n"
    "wgmma.mma_async.sync.aligned.m64n256k16.f32.bf16.bf16 {%0, %1, %2, %3, %4, %5, %6, %7, %8, %9, %10, %11, %12, %13, %14, %15, %16, %17, %18, %19, %20, %21, %22, %23, %24, %25, %26, %27, %28, %29, %30, %31, %32, %33, %34, %35, %36, %37, %38, %39, %40, %41, %42, %43, %44, %45, %46, %47, %48, %49, %50, %51, %52, %53, %54, %55, %56, %57, %58, %59, %60, %61, %62, %63, %64, %65, %66, %67, %68, %69, %70, %71, %72, %73, %74, %75, %76, %77, %78, %79, %80, %81, %82, %83, %84, %85, %86, %87, %88, %89, %90, %91, %92, %93, %94, %95, %96, %97, %98, %99, %100, %101, %102, %103, %104, %105, %106, %107, %108, %109, %110, %111, %112, %113, %114, %115, %116, %117, %118, %119, %120, %121, %122, %123, %124, %125, %126, %127}, {%128, %129, %130, %131}, %132, p, 1, 1, 1;\n}\n"
    : "+f"(d[0]), "+f"(d[1]), "+f"(d[2]), "+f"(d[3]), "+f"(d[4]), "+f"(d[5]), "+f"(d[6]), "+f"(d[7]), "+f"(d[8]), "+f"(d[9]), "+f"(d[10]), "+f"(d[11]), "+f"(d[12]), "+f"(d[13]), "+f"(d[14]), "+f"(d[15]), "+f"(d[16]), "+f"(d[17]), "+f"(d[18]), "+f"(d[19]), "+f"(d[20]), "+f"(d[21]), "+f"(d[22]), "+f"(d[23]), "+f"(d[24]), "+f"(d[25]), "+f"(d[26]), "+f"(d[27]), "+f"(d[28]), "+f"(d[29]), "+f"(d[30]), "+f"(d[31]), "+f"(d[32]), "+f"(d[33]), "+f"(d[34]), "+f"(d[35]), "+f"(d[36]), "+f"(d[37]), "+f"(d[38]), "+f"(d[39]), "+f"(d[40]), "+f"(d[41]), "+f"(d[42]), "+f"(d[43]), "+f"(d[44]), "+f"(d[45]), "+f"(d[46]), "+f"(d[47]), "+f"(d[48]), "+f"(d[49]), "+f"(d[50]), "+f"(d[51]), "+f"(d[52]), "+f"(d[53]), "+f"(d[54]), "+f"(d[55]), "+f"(d[56]), "+f"(d[57]), "+f"(d[58]), "+f"(d[59]), "+f"(d[60]), "+f"(d[61]), "+f"(d[62]), "+f"(d[63]), "+f"(d[64]), "+f"(d[65]), "+f"(d[66]), "+f"(d[67]), "+f"(d[68]), "+f"(d[69]), "+f"(d[70]), "+f"(d[71]), "+f"(d[72]), "+f"(d[73]), "+f"(d[74]), "+f"(d[75]), "+f"(d[76]), "+f"(d[77]), "+f"(d[78]), "+f"(d[79]), "+f"(d[80]), "+f"(d[81]), "+f"(d[82]), "+f"(d[83]), "+f"(d[84]), "+f"(d[85]), "+f"(d[86]), "+f"(d[87]), "+f"(d[88]), "+f"(d[89]), "+f"(d[90]), "+f"(d[91]), "+f"(d[92]), "+f"(d[93]), "+f"(d[94]), "+f"(d[95]), "+f"(d[96]), "+f"(d[97]), "+f"(d[98]), "+f"(d[99]), "+f"(d[100]), "+f"(d[101]), "+f"(d[102]), "+f"(d[103]), "+f"(d[104]), "+f"(d[105]), "+f"(d[106]), "+f"(d[107]), "+f"(d[108]), "+f"(d[109]), "+f"(d[110]), "+f"(d[111]), "+f"(d[112]), "+f"(d[113]), "+f"(d[114]), "+f"(d[115]), "+f"(d[116]), "+f"(d[117]), "+f"(d[118]), "+f"(d[119]), "+f"(d[120]), "+f"(d[121]), "+f"(d[122]), "+f"(d[123]), "+f"(d[124]), "+f"(d[125]), "+f"(d[126]), "+f"(d[127])
    : "r"(a0), "r"(a1), "r"(a2), "r"(a3), "l"(db), "r"(sc));
}
__device__ __forceinline__ void wgmma_m64n192k16_ss_tb(float (&d)[96], uint64_t da, uint64_t db, int sc) {
  asm volatile("{\n.reg .pred p;\nsetp.ne.b32 p, %98, 0;\n"
    "wgmma.mma_async.sync.aligned.m64n192k16.f32.bf16.bf16 {%0, %1, %2, %3, %4, %5, %6, %7, %8, %9, %10, %11, %12, %13, %14, %15, %16, %17, %18, %19, %20, %21, %22, %23, %24, %25, %26, %27, %28, %29, %30, %31, %32, %33, %34, %35, %36, %37, %38, %39, %40, %41, %42, %43, %44, %45, %46, %47, %48, %49, %50, %51, %52, %53, %54, %55, %56, %57, %58, %59, %60, %61, %62, %63, %64, %65, %66, %67, %68, %69, %70, %71, %72, %73, %74, %75, %76, %77, %78, %79, %80, %81, %82, %83, %84, %85, %86, %87, %88, %89, %90, %91, %92, %93, %94, %95}, %96, %97, p, 1, 1, 0, 1;\n}\n"
    : "+f"(d[0]), "+f"(d[1]), "+f"(d[2]), "+f"(d[3]), "+f"(d[4]), "+f"(d[5]), "+f"(d[6]), "+f"(d[7]), "+f"(d[8]), "+f"(d[9]), "+f"(d[10]), "+f"(d[11]), "+f"(d[12]), "+f"(d[13]), "+f"(d[14]), "+f"(d[15]), "+f"(d[16]), "+f"(d[17]), "+f"(d[18]), "+f"(d[19]), "+f"(d[20]), "+f"(d[21]), "+f"(d[22]), "+f"(d[23]), "+f"(d[24]), "+f"(d[25]), "+f"(d[26]), "+f"(d[27]), "+f"(d[28]), "+f"(d[29]), "+f"(d[30]), "+f"(d[31]), "+f"(d[32]), "+f"(d[33]), "+f"(d[34]), "+f"(d[35]), "+f"(d[36]), "+f"(d[37]), "+f"(d[38]), "+f"(d[39]), "+f"(d[40]), "+f"(d[41]), "+f"(d[42]), "+f"(d[43]), "+f"(d[44]), "+f"(d[45]), "+f"(d[46]), "+f"(d[47]), "+f"(d[48]), "+f"(d[49]), "+f"(d[50]), "+f"(d[51]), "+f"(d[52]), "+f"(d[53]), "+f"(d[54]), "+f"(d[55]), "+f"(d[56]), "+f"(d[57]), "+f"(d[58]), "+f"(d[59]), "+f"(d[60]), "+f"(d[61]), "+f"(d[62]), "+f"(d[63]), "+f"(d[64]), "+f"(d[65]), "+f"(d[66]), "+f"(d[67]), "+f"(d[68]), "+f"(d[69]), "+f"(d[70]), "+f"(d[71]), "+f"(d[72]), "+f"(d[73]), "+f"(d[74]), "+f"(d[75]), "+f"(d[76]), "+f"(d[77]), "+f"(d[78]), "+f"(d[79]), "+f"(d[80]), "+f"(d[81]), "+f"(d[82]), "+f"(d[83]), "+f"(d[84]), "+f"(d[85]), "+f"(d[86]), "+f"(d[87]), "+f"(d[88]), "+f"(d[89]), "+f"(d[90]), "+f"(d[91]), "+f"(d[92]), "+f"(d[93]), "+f"(d[94]), "+f"(d[95])
    : "l"(da), "l"(db), "r"(sc));
}
__device__ __forceinline__ void wgmma_m64n192k16_rs_tb(float (&d)[96], uint32_t a0, uint32_t a1, uint32_t a2, uint32_t a3, uint64_t db, int sc) {
  asm volatile("{\n.reg .pred p;\nsetp.ne.b32 p, %101, 0;\n"
    "wgmma.mma_async.sync.aligned.m64n192k16.f32.bf16.bf16 {%0, %1, %2, %3, %4, %5, %6, %7, %8, %9, %10, %11, %12, %13, %14, %15, %16, %17, %18, %19, %20, %21, %22, %23, %24, %25, %26, %27, %28, %29, %30, %31, %32, %33, %34, %35, %36, %37, %38, %39, %40, %41, %42, %43, %44, %45, %46, %47, %48, %49, %50, %51, %52, %53, %54, %55, %56, %57, %58, %59, %60, %61, %62, %63, %64, %65, %66, %67, %68, %69, %70, %71, %72, %73, %74, %75, %76, %77, %78, %79, %80, %81, %82, %83, %84, %85, %86, %87, %88, %89, %90, %91, %92, %93, %94, %95}, {%96, %97, %98, %99}, %100, p, 1, 1, 1;\n}\n"
    : "+f"(d[0]), "+f"(d[1]), "+f"(d[2]), "+f"(d[3]), "+f"(d[4]), "+f"(d[5]), "+f"(d[6]), "+f"(d[7]), "+f"(d[8]), "+f"(d[9]), "+f"(d[10]), "+f"(d[11]), "+f"(d[12]), "+f"(d[13]), "+f"(d[14]), "+f"(d[15]), "+f"(d[16]), "+f"(d[17]), "+f"(d[18]), "+f"(d[19]), "+f"(d[20]), "+f"(d[21]), "+f"(d[22]), "+f"(d[23]), "+f"(d[24]), "+f"(d[25]), "+f"(d[26]), "+f"(d[27]), "+f"(d[28]), "+f"(d[29]), "+f"(d[30]), "+f"(d[31]), "+f"(d[32]), "+f"(d[33]), "+f"(d[34]), "+f"(d[35]), "+f"(d[36]), "+f"(d[37]), "+f"(d[38]), "+f"(d[39]), "+f"(d[40]), "+f"(d[41]), "+f"(d[42]), "+f"(d[43]), "+f"(d[44]), "+f"(d[45]), "+f"(d[46]), "+f"(d[47]), "+f"(d[48]), "+f"(d[49]), "+f"(d[50]), "+f"(d[51]), "+f"(d[52]), "+f"(d[53]), "+f"(d[54]), "+f"(d[55]), "+f"(d[56]), "+f"(d[57]), "+f"(d[58]), "+f"(d[59]), "+f"(d[60]), "+f"(d[61]), "+f"(d[62]), "+f"(d[63]), "+f"(d[64]), "+f"(d[65]), "+f"(d[66]), "+f"(d[67]), "+f"(d[68]), "+f"(d[69]), "+f"(d[70]), "+f"(d[71]), "+f"(d[72]), "+f"(d[73]), "+f"(d[74]), "+f"(d[75]), "+f"(d[76]), "+f"(d[77]), "+f"(d[78]), "+f"(d[79]), "+f"(d[80]), "+f"(d[81]), "+f"(d[82]), "+f"(d[83]), "+f"(d[84]), "+f"(d[85]), "+f"(d[86]), "+f"(d[87]), "+f"(d[88]), "+f"(d[89]), "+f"(d[90]), "+f"(d[91]), "+f"(d[92]), "+f"(d[93]), "+f"(d[94]), "+f"(d[95])
    : "r"(a0), "r"(a1), "r"(a2), "r"(a3), "l"(db), "r"(sc));
}


constexpr int NS = 5;
constexpr uint32_t STG = 32768;
constexpr uint32_t SM_Q = 0;
constexpr uint32_t SM_RING = 65536;
constexpr uint32_t SM_BAR = SM_RING + NS * STG;
constexpr uint32_t SM_TOTAL = SM_BAR + 256 + 1024;

struct Ring {
  uint32_t base, full0, empty0; int it;
  __device__ __forceinline__ uint32_t stage() const { return (uint32_t)(it % NS); }
  __device__ __forceinline__ uint32_t phase() const { return (uint32_t)((it / NS) & 1); }
  __device__ __forceinline__ uint32_t buf() const { return base + stage() * STG; }
  __device__ __forceinline__ uint32_t full() const { return full0 + stage() * 8; }
  __device__ __forceinline__ uint32_t empty() const { return empty0 + stage() * 8; }
  __device__ __forceinline__ uint32_t acquire(uint32_t bytes) {
    mbar_wait_cluster(empty(), phase() ^ 1); mbar_expect_tx(full(), bytes); return buf();
  }
  __device__ __forceinline__ uint32_t wait() { mbar_wait(full(), phase()); return buf(); }
};
__device__ __forceinline__ void ring_release(uint32_t empty_bar, int lane) {
  __syncwarp();
  if (lane < 2) mbar_arrive_remote(empty_bar, (uint32_t)lane);
}

__device__ __forceinline__ void gemm_k448_n256(Ring& r, float (&acc)[128], int wg, int lane) {
#pragma unroll 1
  for (int p = 0; p < 4; ++p) {
    uint32_t hb = r.wait(); uint32_t hrel = r.empty(); r.it++;
    int nc = (p < 3) ? 2 : 1;
#pragma unroll 1
    for (int c = 0; c < nc; ++c) {
      uint32_t wb = r.wait(); uint32_t wrel = r.empty(); r.it++;
      uint64_t da = mk_desc(hb + c * 16384 + wg * 8192, 16, 1024);
      uint64_t db = mk_desc(wb, 8192, 1024);
      wg_fence();
#pragma unroll
      for (int k = 0; k < 4; ++k) wgmma_m64n256k16_ss_tb(acc, da + k * 2, db + k * 128, (p | c | k) != 0);
      wg_commit(); wg_wait<0>();
      ring_release(wrel, lane);
    }
    ring_release(hrel, lane);
  }
}

template <int NREG>
__device__ __forceinline__ void red_out(float* dst_row0, float (&acc)[NREG], int t) {
#pragma unroll
  for (int j = 0; j < NREG / 4; ++j) {
    red_add_v2(dst_row0 + 8 * j + 2 * t, acc[4 * j], acc[4 * j + 1]);
    red_add_v2(dst_row0 + 8 * DM + 8 * j + 2 * t, acc[4 * j + 2], acc[4 * j + 3]);
  }
}

__global__ void __cluster_dims__(2, 1, 1) __launch_bounds__(384, 1)
attn_kernel(const __grid_constant__ CUtensorMap tm_h, const __grid_constant__ CUtensorMap tm_wq,
            const __grid_constant__ CUtensorMap tm_k, const __grid_constant__ CUtensorMap tm_v,
            const __grid_constant__ CUtensorMap tm_wo, const __grid_constant__ CUtensorMap tm_oA) {
  extern __shared__ uint8_t smem_raw[];
  const uint32_t sb = (smem_u32(smem_raw) + 1023) & ~1023u;
  const int tid = threadIdx.x, wg = tid >> 7, lane = tid & 31;
  const int qt = blockIdx.x, kvh = blockIdx.y;
  const uint32_t rank = cluster_rank();
  Ring r; r.base = sb + SM_RING; r.full0 = sb + SM_BAR; r.empty0 = sb + SM_BAR + 64; r.it = 0;
  const uint32_t bar_oA = sb + SM_BAR + 128;
  if (tid == 0) {
    for (int i = 0; i < NS; ++i) { mbar_init(r.full0 + 8 * i, 1); mbar_init(r.empty0 + 8 * i, 16); }
    mbar_init(bar_oA, 256);
    asm volatile("fence.mbarrier_init.release.cluster;" ::: "memory");
  }
  cluster_sync_all();
  pdl_wait();

  if (wg == 2) {
    asm volatile("setmaxnreg.dec.sync.aligned.u32 24;");
    if (tid == 256) {
      const int krow0 = kvh * SKV + (SKV - WIN);
      for (int hh = 0; hh < 2; ++hh) {
        const int head = kvh * 2 + hh;
        for (int p = 0; p < 4; ++p) {
          int nc = (p < 3) ? 2 : 1;
          uint32_t b = r.acquire(nc * 16384);
          for (int c = 0; c < nc; ++c) tma_load(b + c * 16384, &tm_h, (2 * p + c) * 64, qt * 128, r.full());
          r.it++;
          for (int c = 0; c < nc; ++c) {
            b = r.acquire(32768);
            for (int x = 0; x < 2; ++x) {
              int bx = rank * 2 + x;
              tma_load_mc(b + bx * 8192, &tm_wq, head * 256 + bx * 64, (2 * p + c) * 64, r.full(), 3);
            }
            r.it++;
          }
        }
        for (int t = 0; t < 4; ++t) {
          for (int hf = 0; hf < 2; ++hf) {
            uint32_t b = r.acquire(32768);
            tma_load_mc(b + rank * 16384, &tm_k, (2 * hf + rank) * 64, krow0 + t * 128, r.full(), 3);
            r.it++;
          }
          for (int hf = 0; hf < 2; ++hf) {
            uint32_t b = r.acquire(32768);
            for (int x = 0; x < 2; ++x) {
              int bx = rank * 2 + x;
              tma_load_mc(b + bx * 8192, &tm_v, bx * 64, krow0 + t * 128 + hf * 64, r.full(), 3);
            }
            r.it++;
          }
        }
      }
      mbar_wait(bar_oA, 0);
      for (int half = 0; half < 2; ++half) {
        const int nb = half ? 3 : 4;
        for (int c = 0; c < 8; ++c) {
          if (c < 4 && (c & 1) == 0) {
            uint32_t b = r.acquire(32768);
            tma_load(b, &tm_oA, c * 64, kvh * SEQ + qt * 128, r.full());
            tma_load(b + 16384, &tm_oA, (c + 1) * 64, kvh * SEQ + qt * 128, r.full());
            r.it++;
          }
          uint32_t b = r.acquire(nb * 8192);
          for (int x = 0; x < 2; ++x) {
            int bx = rank * 2 + x;
            if (bx < nb) tma_load_mc(b + bx * 8192, &tm_wo, half * 256 + bx * 64, kvh * 512 + c * 64, r.full(), 3);
          }
          r.it++;
        }
      }
    }
  } else {
    asm volatile("setmaxnreg.inc.sync.aligned.u32 240;");
    const int warp = (tid >> 5) & 3, g = lane >> 2, t4 = lane & 3;
    const int rloc = wg * 64 + warp * 16 + g;
    uint32_t ob[64];
    const float CS = 1.4426950408889634f * 0.0625f;
#pragma unroll 1
    for (int hh = 0; hh < 2; ++hh) {
      float acc[128];
      gemm_k448_n256(r, acc, wg, lane);
      {
        uint32_t qrow0 = sb + SM_Q + rloc * 128, qrow1 = qrow0 + 8 * 128;
        uint32_t sw = (uint32_t)(rloc & 7);
#pragma unroll
        for (int j = 0; j < 32; ++j) {
          uint32_t off = (uint32_t)(j >> 3) * 16384 + ((((uint32_t)j & 7) ^ sw) << 4) + t4 * 4;
          asm volatile("st.shared.b32 [%0], %1;" ::"r"(qrow0 + off), "r"(pack_bf16(acc[4 * j], acc[4 * j + 1])) : "memory");
          asm volatile("st.shared.b32 [%0], %1;" ::"r"(qrow1 + off), "r"(pack_bf16(acc[4 * j + 2], acc[4 * j + 3])) : "memory");
        }
      }
      fence_async();
      bar_sync(1 + wg, 128);
      float m0 = -INFINITY, m1 = -INFINITY, l0 = 0.f, l1 = 0.f;
#pragma unroll 1
      for (int t = 0; t < 4; ++t) {
        float s[64];
        {
          uint32_t ka = r.wait(); uint32_t rel0 = r.empty(); r.it++;
          wg_fence();
#pragma unroll
          for (int k = 0; k < 8; ++k)
            wgmma_m64n128k16_ss(s, mk_desc(sb + SM_Q + (k >> 2) * 16384 + wg * 8192 + (k & 3) * 32, 16, 1024),
                                mk_desc(ka + (k >> 2) * 16384 + (k & 3) * 32, 16, 1024), k != 0);
          wg_commit();
          uint32_t kb = r.wait(); uint32_t rel1 = r.empty(); r.it++;
#pragma unroll
          for (int k = 0; k < 8; ++k)
            wgmma_m64n128k16_ss(s, mk_desc(sb + SM_Q + (2 + (k >> 2)) * 16384 + wg * 8192 + (k & 3) * 32, 16, 1024),
                                mk_desc(kb + (k >> 2) * 16384 + (k & 3) * 32, 16, 1024), 1);
          wg_commit(); wg_wait<0>();
          ring_release(rel0, lane); ring_release(rel1, lane);
        }
        float mx0 = m0, mx1 = m1;
#pragma unroll
        for (int j = 0; j < 16; ++j) {
          uint32_t a = pack_bf16(s[4 * j], s[4 * j + 1]), b = pack_bf16(s[4 * j + 2], s[4 * j + 3]);
          s[4 * j] = bf_lo(a); s[4 * j + 1] = bf_hi(a); s[4 * j + 2] = bf_lo(b); s[4 * j + 3] = bf_hi(b);
          mx0 = fmaxf(mx0, fmaxf(s[4 * j], s[4 * j + 1])); mx1 = fmaxf(mx1, fmaxf(s[4 * j + 2], s[4 * j + 3]));
        }
        mx0 = fmaxf(mx0, __shfl_xor_sync(0xffffffffu, mx0, 1)); mx0 = fmaxf(mx0, __shfl_xor_sync(0xffffffffu, mx0, 2));
        mx1 = fmaxf(mx1, __shfl_xor_sync(0xffffffffu, mx1, 1)); mx1 = fmaxf(mx1, __shfl_xor_sync(0xffffffffu, mx1, 2));
        const float c0 = ex2((m0 - mx0) * CS), c1 = ex2((m1 - mx1) * CS);
        m0 = mx0; m1 = mx1;
        const float nb0 = -mx0 * CS, nb1 = -mx1 * CS;
        float ps0 = 0.f, ps1 = 0.f;
        uint32_t pa[32];
#pragma unroll
        for (int j = 0; j < 16; ++j) {
          float e0 = ex2(fmaf(s[4 * j], CS, nb0)), e1 = ex2(fmaf(s[4 * j + 1], CS, nb0));
          float e2 = ex2(fmaf(s[4 * j + 2], CS, nb1)), e3 = ex2(fmaf(s[4 * j + 3], CS, nb1));
          ps0 += e0 + e1; ps1 += e2 + e3;
          pa[2 * j] = pack_bf16(e0, e1); pa[2 * j + 1] = pack_bf16(e2, e3);
        }
        l0 = l0 * c0 + ps0; l1 = l1 * c1 + ps1;
        if (t > 0) {
#pragma unroll
          for (int j = 0; j < 32; ++j) { acc[4 * j] *= c0; acc[4 * j + 1] *= c0; acc[4 * j + 2] *= c1; acc[4 * j + 3] *= c1; }
        }
        {
          uint32_t va = r.wait(); uint32_t rel0 = r.empty(); r.it++;
          wg_fence();
#pragma unroll
          for (int k = 0; k < 4; ++k)
            wgmma_m64n256k16_rs_tb(acc, pa[4 * k], pa[4 * k + 1], pa[4 * k + 2], pa[4 * k + 3],
                                   mk_desc(va + k * 2048, 8192, 1024), (t | k) != 0);
          wg_commit();
          uint32_t vb = r.wait(); uint32_t rel1 = r.empty(); r.it++;
#pragma unroll
          for (int k = 0; k < 4; ++k)
            wgmma_m64n256k16_rs_tb(acc, pa[16 + 4 * k], pa[16 + 4 * k + 1], pa[16 + 4 * k + 2], pa[16 + 4 * k + 3],
                                   mk_desc(vb + k * 2048, 8192, 1024), 1);
          wg_commit(); wg_wait<0>();
          ring_release(rel0, lane); ring_release(rel1, lane);
        }
      }
      l0 += __shfl_xor_sync(0xffffffffu, l0, 1); l0 += __shfl_xor_sync(0xffffffffu, l0, 2);
      l1 += __shfl_xor_sync(0xffffffffu, l1, 1); l1 += __shfl_xor_sync(0xffffffffu, l1, 2);
      const float i0 = 1.f / l0, i1 = 1.f / l1;
#pragma unroll
      for (int j = 0; j < 32; ++j) {
        ob[2 * j] = pack_bf16(acc[4 * j] * i0, acc[4 * j + 1] * i0);
        ob[2 * j + 1] = pack_bf16(acc[4 * j + 2] * i1, acc[4 * j + 3] * i1);
      }
      if (hh == 0) {
        uint32_t* o0 = reinterpret_cast<uint32_t*>(g_oA + ((size_t)kvh * SEQ + qt * 128 + rloc) * DH) + t4;
#pragma unroll
        for (int j = 0; j < 32; ++j) { o0[4 * j] = ob[2 * j]; o0[4 * j + 8 * DH / 2] = ob[2 * j + 1]; }
        fence_async();
        mbar_arrive(bar_oA);
      }
    }
    float* dst = g_acc1 + (size_t)(qt * 128 + rloc) * DM;
    {
      float acc[128];
#pragma unroll 1
      for (int p = 0; p < 2; ++p) {
        uint32_t ab = r.wait(); uint32_t arel = r.empty(); r.it++;
#pragma unroll 1
        for (int c = 0; c < 2; ++c) {
          uint32_t wb = r.wait(); uint32_t wrel = r.empty(); r.it++;
          uint64_t da = mk_desc(ab + c * 16384 + wg * 8192, 16, 1024), db = mk_desc(wb, 8192, 1024);
          wg_fence();
#pragma unroll
          for (int k = 0; k < 4; ++k) wgmma_m64n256k16_ss_tb(acc, da + k * 2, db + k * 128, (p | c | k) != 0);
          wg_commit(); wg_wait<0>();
          ring_release(wrel, lane);
        }
        ring_release(arel, lane);
      }
#pragma unroll
      for (int c = 0; c < 4; ++c) {
        uint32_t wb = r.wait(); uint32_t wrel = r.empty(); r.it++;
        uint64_t db = mk_desc(wb, 8192, 1024);
        wg_fence();
#pragma unroll
        for (int k = 0; k < 4; ++k)
          wgmma_m64n256k16_rs_tb(acc, ob[16 * c + 4 * k], ob[16 * c + 4 * k + 1], ob[16 * c + 4 * k + 2], ob[16 * c + 4 * k + 3], db + k * 128, 1);
        wg_commit(); wg_wait<0>();
        ring_release(wrel, lane);
      }
      red_out<128>(dst, acc, t4);
    }
    {
      float acc[96];
#pragma unroll 1
      for (int p = 0; p < 2; ++p) {
        uint32_t ab = r.wait(); uint32_t arel = r.empty(); r.it++;
#pragma unroll 1
        for (int c = 0; c < 2; ++c) {
          uint32_t wb = r.wait(); uint32_t wrel = r.empty(); r.it++;
          uint64_t da = mk_desc(ab + c * 16384 + wg * 8192, 16, 1024), db = mk_desc(wb, 8192, 1024);
          wg_fence();
#pragma unroll
          for (int k = 0; k < 4; ++k) wgmma_m64n192k16_ss_tb(acc, da + k * 2, db + k * 128, (p | c | k) != 0);
          wg_commit(); wg_wait<0>();
          ring_release(wrel, lane);
        }
        ring_release(arel, lane);
      }
#pragma unroll
      for (int c = 0; c < 4; ++c) {
        uint32_t wb = r.wait(); uint32_t wrel = r.empty(); r.it++;
        uint64_t db = mk_desc(wb, 8192, 1024);
        wg_fence();
#pragma unroll
        for (int k = 0; k < 4; ++k)
          wgmma_m64n192k16_rs_tb(acc, ob[16 * c + 4 * k], ob[16 * c + 4 * k + 1], ob[16 * c + 4 * k + 2], ob[16 * c + 4 * k + 3], db + k * 128, 1);
        wg_commit(); wg_wait<0>();
        ring_release(wrel, lane);
      }
      red_out<96>(dst + 256, acc, t4);
    }
  }
  cluster_sync_all();
}

__global__ void __cluster_dims__(2, 1, 1) __launch_bounds__(384, 1)
ffn_kernel(const __grid_constant__ CUtensorMap tm_h2, const __grid_constant__ CUtensorMap tm_w1,
           const __grid_constant__ CUtensorMap tm_w2) {
  extern __shared__ uint8_t smem_raw[];
  const uint32_t sb = (smem_u32(smem_raw) + 1023) & ~1023u;
  const int tid = threadIdx.x, wg = tid >> 7, lane = tid & 31;
  const int rt = blockIdx.x, sl = blockIdx.y;
  const uint32_t rank = cluster_rank();
  Ring r; r.base = sb + SM_RING; r.full0 = sb + SM_BAR; r.empty0 = sb + SM_BAR + 64; r.it = 0;
  if (tid == 0) {
    for (int i = 0; i < NS; ++i) { mbar_init(r.full0 + 8 * i, 1); mbar_init(r.empty0 + 8 * i, 16); }
    asm volatile("fence.mbarrier_init.release.cluster;" ::: "memory");
  }
  cluster_sync_all();
  pdl_wait();
  if (wg == 2) {
    asm volatile("setmaxnreg.dec.sync.aligned.u32 24;");
    if (tid == 256) {
      for (int p = 0; p < 4; ++p) {
        int nc = (p < 3) ? 2 : 1;
        uint32_t b = r.acquire(nc * 16384);
        for (int c = 0; c < nc; ++c) tma_load(b + c * 16384, &tm_h2, (2 * p + c) * 64, rt * 128, r.full());
        r.it++;
        for (int c = 0; c < nc; ++c) {
          b = r.acquire(32768);
          for (int x = 0; x < 2; ++x) {
            int bx = rank * 2 + x;
            tma_load_mc(b + bx * 8192, &tm_w1, sl * 256 + bx * 64, (2 * p + c) * 64, r.full(), 3);
          }
          r.it++;
        }
      }
      for (int half = 0; half < 2; ++half) {
        const int nb = half ? 3 : 4;
        for (int c = 0; c < 4; ++c) {
          uint32_t b = r.acquire(nb * 8192);
          for (int x = 0; x < 2; ++x) {
            int bx = rank * 2 + x;
            if (bx < nb) tma_load_mc(b + bx * 8192, &tm_w2, half * 256 + bx * 64, sl * 256 + c * 64, r.full(), 3);
          }
          r.it++;
        }
      }
    }
  } else {
    asm volatile("setmaxnreg.inc.sync.aligned.u32 240;");
    const int warp = (tid >> 5) & 3, g = lane >> 2, t4 = lane & 3;
    const int rloc = wg * 64 + warp * 16 + g;
    uint32_t ob[64];
    {
      float acc[128];
      gemm_k448_n256(r, acc, wg, lane);
#pragma unroll
      for (int j = 0; j < 32; ++j) {
        ob[2 * j] = pack_bf16(fmaxf(acc[4 * j], 0.f), fmaxf(acc[4 * j + 1], 0.f));
        ob[2 * j + 1] = pack_bf16(fmaxf(acc[4 * j + 2], 0.f), fmaxf(acc[4 * j + 3], 0.f));
      }
    }
    float* dst = g_acc2 + (size_t)(rt * 128 + rloc) * DM;
    {
      float acc[128];
#pragma unroll
      for (int c = 0; c < 4; ++c) {
        uint32_t wb = r.wait(); uint32_t wrel = r.empty(); r.it++;
        uint64_t db = mk_desc(wb, 8192, 1024);
        wg_fence();
#pragma unroll
        for (int k = 0; k < 4; ++k)
          wgmma_m64n256k16_rs_tb(acc, ob[16 * c + 4 * k], ob[16 * c + 4 * k + 1], ob[16 * c + 4 * k + 2], ob[16 * c + 4 * k + 3], db + k * 128, (c | k) != 0);
        wg_commit(); wg_wait<0>();
        ring_release(wrel, lane);
      }
      red_out<128>(dst, acc, t4);
    }
    {
      float acc[96];
#pragma unroll
      for (int c = 0; c < 4; ++c) {
        uint32_t wb = r.wait(); uint32_t wrel = r.empty(); r.it++;
        uint64_t db = mk_desc(wb, 8192, 1024);
        wg_fence();
#pragma unroll
        for (int k = 0; k < 4; ++k)
          wgmma_m64n192k16_rs_tb(acc, ob[16 * c + 4 * k], ob[16 * c + 4 * k + 1], ob[16 * c + 4 * k + 2], ob[16 * c + 4 * k + 3], db + k * 128, (c | k) != 0);
        wg_commit(); wg_wait<0>();
        ring_release(wrel, lane);
      }
      red_out<96>(dst + 256, acc, t4);
    }
  }
  cluster_sync_all();
}

__global__ void __launch_bounds__(256) mod_kernel(const __nv_bfloat16* __restrict__ c, const __nv_bfloat16* __restrict__ wm) {
  __shared__ float sc[DM];
  __shared__ float red[8][64];
  const int tid = threadIdx.x;
  {
    float4 z = make_float4(0.f, 0.f, 0.f, 0.f);
    const int n4 = SEQ * DM / 4;
    for (int i = blockIdx.x * 256 + tid; i < n4; i += gridDim.x * 256) {
      reinterpret_cast<float4*>(g_acc1)[i] = z; reinterpret_cast<float4*>(g_acc2)[i] = z;
    }
  }
  if (blockIdx.x < 42) {
    for (int i = tid; i < DM; i += 256) {
      float v = __bfloat162float(c[i]);
      sc[i] = rbf(v / (1.f + __expf(-v)));
    }
    __syncthreads();
    const int w = tid >> 5, lane = tid & 31;
    const int col = blockIdx.x * 64 + lane * 2;
    float a0 = 0.f, a1 = 0.f;
#pragma unroll 8
    for (int k = w * 56; k < w * 56 + 56; ++k) {
      uint32_t v = *reinterpret_cast<const uint32_t*>(wm + (size_t)k * (6 * DM) + col);
      a0 = fmaf(sc[k], bf_lo(v), a0); a1 = fmaf(sc[k], bf_hi(v), a1);
    }
    red[w][lane * 2] = a0; red[w][lane * 2 + 1] = a1;
    __syncthreads();
    if (tid < 64) {
      float s = 0.f;
#pragma unroll
      for (int i = 0; i < 8; ++i) s += red[i][tid];
      g_mod[blockIdx.x * 64 + tid] = rbf(s);
    }
  }
  pdl_launch();
}

__device__ __forceinline__ void ln_row(const float (&x)[14], const float* __restrict__ shift, const float* __restrict__ scale,
                                       __nv_bfloat16* __restrict__ out, int lane) {
  float s = 0.f;
#pragma unroll
  for (int i = 0; i < 14; ++i) s += x[i];
#pragma unroll
  for (int o = 16; o; o >>= 1) s += __shfl_xor_sync(0xffffffffu, s, o);
  const float mean = s * (1.f / DM);
  float q = 0.f;
#pragma unroll
  for (int i = 0; i < 14; ++i) { float d = x[i] - mean; q = fmaf(d, d, q); }
#pragma unroll
  for (int o = 16; o; o >>= 1) q += __shfl_xor_sync(0xffffffffu, q, o);
  const float mb = rbf(mean), vb = rbf(q * (1.f / DM));
  const float den = rbf(sqrtf(rbf(vb + 1e-5f)));
#pragma unroll
  for (int i = 0; i < 7; ++i) {
    int col = i * 64 + lane * 2;
    float y0 = rbf(rbf(x[2 * i] - mb) / den), y1 = rbf(rbf(x[2 * i + 1] - mb) / den);
    y0 = rbf(y0 * rbf(1.f + scale[col])); y1 = rbf(y1 * rbf(1.f + scale[col + 1]));
    *reinterpret_cast<uint32_t*>(out + col) = pack_bf16(y0 + shift[col], y1 + shift[col + 1]);
  }
}

__global__ void __launch_bounds__(256) ln1_kernel(const __nv_bfloat16* __restrict__ x) {
  pdl_wait();
  const int lane = threadIdx.x & 31, row = blockIdx.x * 8 + (threadIdx.x >> 5);
  float v[14];
#pragma unroll
  for (int i = 0; i < 7; ++i) {
    uint32_t u = *reinterpret_cast<const uint32_t*>(x + (size_t)row * DM + i * 64 + lane * 2);
    v[2 * i] = bf_lo(u); v[2 * i + 1] = bf_hi(u);
  }
  ln_row(v, g_mod + 0 * DM, g_mod + 1 * DM, g_h + (size_t)row * DM, lane);
  pdl_launch();
}

__global__ void __launch_bounds__(256) ln2_kernel(const __nv_bfloat16* __restrict__ x) {
  pdl_wait();
  const int lane = threadIdx.x & 31, row = blockIdx.x * 8 + (threadIdx.x >> 5);
  float v[14];
#pragma unroll
  for (int i = 0; i < 7; ++i) {
    int col = i * 64 + lane * 2;
    uint32_t u = *reinterpret_cast<const uint32_t*>(x + (size_t)row * DM + col);
    float2 a = *reinterpret_cast<const float2*>(g_acc1 + (size_t)row * DM + col);
    float t0 = rbf(g_mod[2 * DM + col] * rbf(a.x)), t1 = rbf(g_mod[2 * DM + col + 1] * rbf(a.y));
    v[2 * i] = rbf(bf_lo(u) + t0); v[2 * i + 1] = rbf(bf_hi(u) + t1);
    *reinterpret_cast<uint32_t*>(g_x1 + (size_t)row * DM + col) = pack_bf16(v[2 * i], v[2 * i + 1]);
  }
  ln_row(v, g_mod + 3 * DM, g_mod + 4 * DM, g_h2 + (size_t)row * DM, lane);
  pdl_launch();
}

__global__ void __launch_bounds__(256) final_kernel(__nv_bfloat16* __restrict__ out) {
  pdl_wait();
  const int i = blockIdx.x * 256 + threadIdx.x;
  const int col = (i * 2) % DM;
  uint32_t u = reinterpret_cast<const uint32_t*>(g_x1)[i];
  float2 a = reinterpret_cast<const float2*>(g_acc2)[i];
  float t0 = rbf(g_mod[5 * DM + col] * rbf(a.x)), t1 = rbf(g_mod[5 * DM + col + 1] * rbf(a.y));
  reinterpret_cast<uint32_t*>(out)[i] = pack_bf16(bf_lo(u) + t0, bf_hi(u) + t1);
}

typedef CUresult (*EncodeFn)(CUtensorMap*, CUtensorMapDataType, cuuint32_t, void*, const cuuint64_t*, const cuuint64_t*,
                             const cuuint32_t*, const cuuint32_t*, CUtensorMapInterleave, CUtensorMapSwizzle,
                             CUtensorMapL2promotion, CUtensorMapFloatOOBfill);

static CUtensorMap make_map(EncodeFn enc, const void* ptr, uint64_t cols, uint64_t rows, uint32_t bx, uint32_t by) {
  CUtensorMap m;
  cuuint64_t dims[2] = {cols, rows};
  cuuint64_t strides[1] = {cols * 2};
  cuuint32_t box[2] = {bx, by};
  cuuint32_t es[2] = {1, 1};
  enc(&m, CU_TENSOR_MAP_DATA_TYPE_BFLOAT16, 2, const_cast<void*>(ptr), dims, strides, box, es, CU_TENSOR_MAP_INTERLEAVE_NONE,
      CU_TENSOR_MAP_SWIZZLE_128B, CU_TENSOR_MAP_L2_PROMOTION_L2_256B, CU_TENSOR_MAP_FLOAT_OOB_FILL_NONE);
  return m;
}

template <typename... Args>
static void launch(void (*k)(Args...), dim3 grid, dim3 block, size_t smem, bool pdl, Args... args) {
  cudaLaunchConfig_t cfg = {};
  cfg.gridDim = grid; cfg.blockDim = block; cfg.dynamicSmemBytes = smem; cfg.stream = cudaStreamPerThread;
  cudaLaunchAttribute at[1];
  at[0].id = cudaLaunchAttributeProgrammaticStreamSerialization; at[0].val.programmaticStreamSerializationAllowed = 1;
  cfg.attrs = at; cfg.numAttrs = pdl ? 1 : 0;
  cudaLaunchKernelEx(&cfg, k, args...);
}

extern "C" void kernel_launch(void* const* d_in, const int* in_sizes, int n_in, void* d_out, int out_size) {
  const __nv_bfloat16* x = (const __nv_bfloat16*)d_in[0];
  const void* kc = d_in[1]; const void* vc = d_in[2]; const void* wq = d_in[3]; const void* wo = d_in[4];
  const void* w1 = d_in[6]; const void* w2 = d_in[7];
  const __nv_bfloat16* c = (const __nv_bfloat16*)d_in[8];
  const __nv_bfloat16* wm = (const __nv_bfloat16*)d_in[9];

  void* fn = nullptr; cudaDriverEntryPointQueryResult qr;
  cudaGetDriverEntryPoint("cuTensorMapEncodeTiled", &fn, cudaEnableDefault, &qr);
  EncodeFn enc = (EncodeFn)fn;
  void *p_h, *p_oA, *p_h2;
  cudaGetSymbolAddress(&p_h, g_h); cudaGetSymbolAddress(&p_oA, g_oA); cudaGetSymbolAddress(&p_h2, g_h2);
  CUtensorMap tm_h = make_map(enc, p_h, DM, SEQ, 64, 128);
  CUtensorMap tm_wq = make_map(enc, wq, 4096, DM, 64, 64);
  CUtensorMap tm_k = make_map(enc, kc, DH, HKV * SKV, 64, 128);
  CUtensorMap tm_v = make_map(enc, vc, DH, HKV * SKV, 64, 64);
  CUtensorMap tm_wo = make_map(enc, wo, DM, 4096, 64, 64);
  CUtensorMap tm_oA = make_map(enc, p_oA, DH, HKV * SEQ, 64, 128);
  CUtensorMap tm_h2 = make_map(enc, p_h2, DM, SEQ, 64, 128);
  CUtensorMap tm_w1 = make_map(enc, w1, DFF, DM, 64, 64);
  CUtensorMap tm_w2 = make_map(enc, w2, DM, DFF, 64, 64);
  cudaFuncSetAttribute(attn_kernel, cudaFuncAttributeMaxDynamicSharedMemorySize, SM_TOTAL);
  cudaFuncSetAttribute(ffn_kernel, cudaFuncAttributeMaxDynamicSharedMemorySize, SM_TOTAL);

  launch(mod_kernel, dim3(132), dim3(256), 0, false, c, wm);
  launch(ln1_kernel, dim3(SEQ / 8), dim3(256), 0, true, x);
  launch(attn_kernel, dim3(16, 8), dim3(384), SM_TOTAL, true, tm_h, tm_wq, tm_k, tm_v, tm_wo, tm_oA);
  launch(ln2_kernel, dim3(SEQ / 8), dim3(256), 0, true, x);
  launch(ffn_kernel, dim3(16, 7), dim3(384), SM_TOTAL, true, tm_h2, tm_w1, tm_w2);
  launch(final_kernel, dim3(SEQ * DM / 512), dim3(256), 0, true, (__nv_bfloat16*)d_out);
}
```

```cpp
#include <cuda_runtime.h>
#include <cuda_bf16.h>
#include <cuda.h>
#include <stdint.h>

constexpr int SEQ = 2048, DM = 448, HKV = 8, SKV = 2048, DH = 256, WIN = 512, DFF = 1792;

__device__ __align__(1024) float          g_mod[6 * DM];
__device__ __align__(1024) __nv_bfloat16  g_h[SEQ * DM];
__device__ __align__(1024) __nv_bfloat16  g_oA[HKV * SEQ * DH];
__device__ __align__(1024) float          g_acc1[SEQ * DM];
__device__ __align__(1024) float          g_acc2[SEQ * DM];
__device__ __align__(1024) __nv_bfloat16  g_x1[SEQ * DM];
__device__ __align__(1024) __nv_bfloat16  g_h2[SEQ * DM];

__device__ __forceinline__ uint32_t smem_u32(const void* p) { return (uint32_t)__cvta_generic_to_shared(p); }
__device__ __forceinline__ void mbar_init(uint32_t bar, uint32_t cnt) {
  asm volatile("mbarrier.init.shared::cta.b64 [%0], %1;" ::"r"(bar), "r"(cnt));
}
__device__ __forceinline__ void mbar_expect_tx(uint32_t bar, uint32_t bytes) {
  asm volatile("mbarrier.arrive.expect_tx.shared::cta.b64 _, [%0], %1;" ::"r"(bar), "r"(bytes) : "memory");
}
__device__ __forceinline__ void mbar_arrive(uint32_t bar) {
  asm volatile("mbarrier.arrive.shared::cta.b64 _, [%0];" ::"r"(bar) : "memory");
}
__device__ __forceinline__ void mbar_arrive_remote(uint32_t bar, uint32_t cta) {
  asm volatile("{\n.reg .b32 ra;\nmapa.shared::cluster.u32 ra, %0, %1;\n"
               "mbarrier.arrive.shared::cluster.b64 _, [ra];\n}\n" ::"r"(bar), "r"(cta) : "memory");
}
__device__ __forceinline__ void mbar_wait(uint32_t bar, uint32_t parity) {
  asm volatile("{\n.reg .pred p;\nLAB_WAIT:\n"
               "mbarrier.try_wait.parity.shared::cta.b64 p, [%0], %1, 0x989680;\n"
               "@p bra LAB_DONE;\nbra LAB_WAIT;\nLAB_DONE:\n}\n" ::"r"(bar), "r"(parity) : "memory");
}
__device__ __forceinline__ void mbar_wait_cluster(uint32_t bar, uint32_t parity) {
  asm volatile("{\n.reg .pred p;\nLAB_WAIT:\n"
               "mbarrier.try_wait.parity.acquire.cluster.shared::cta.b64 p, [%0], %1, 0x989680;\n"
               "@p bra LAB_DONE;\nbra LAB_WAIT;\nLAB_DONE:\n}\n" ::"r"(bar), "r"(parity) : "memory");
}
__device__ __forceinline__ void tma_load(uint32_t dst, const CUtensorMap* m, int c0, int c1, uint32_t bar) {
  asm volatile("cp.async.bulk.tensor.2d.shared::cluster.global.mbarrier::complete_tx::bytes [%0], [%1, {%3, %4}], [%2];"
               ::"r"(dst), "l"(m), "r"(bar), "r"(c0), "r"(c1) : "memory");
}
__device__ __forceinline__ void tma_load_mc(uint32_t dst, const CUtensorMap* m, int c0, int c1, uint32_t bar, uint16_t mask) {
  asm volatile("cp.async.bulk.tensor.2d.shared::cluster.global.mbarrier::complete_tx::bytes.multicast::cluster [%0], [%1, {%3, %4}], [%2], %5;"
               ::"r"(dst), "l"(m), "r"(bar), "r"(c0), "r"(c1), "h"(mask) : "memory");
}
__device__ __forceinline__ void cluster_sync_all() {
  asm volatile("barrier.cluster.arrive.release.aligned;\nbarrier.cluster.wait.acquire.aligned;\n" ::: "memory");
}
__device__ __forceinline__ uint32_t cluster_rank() { uint32_t r; asm volatile("mov.u32 %0, %%cluster_ctarank;" : "=r"(r)); return r; }
__device__ __forceinline__ void wg_fence() { asm volatile("wgmma.fence.sync.aligned;" ::: "memory"); }
__device__ __forceinline__ void wg_commit() { asm volatile("wgmma.commit_group.sync.aligned;" ::: "memory"); }
template <int N> __device__ __forceinline__ void wg_wait() { asm volatile("wgmma.wait_group.sync.aligned %0;" ::"n"(N) : "memory"); }
__device__ __forceinline__ void bar_sync(int id, int n) { asm volatile("bar.sync %0, %1;" ::"r"(id), "r"(n) : "memory"); }
__device__ __forceinline__ void bar_arrive(int id, int n) { asm volatile("bar.arrive %0, %1;" ::"r"(id), "r"(n) : "memory"); }
__device__ __forceinline__ void fence_async_smem() { asm volatile("fence.proxy.async.shared::cta;" ::: "memory"); }
__device__ __forceinline__ void fence_async() { asm volatile("fence.proxy.async;" ::: "memory"); }
__device__ __forceinline__ uint64_t mk_desc(uint32_t saddr, uint32_t lbo, uint32_t sbo) {
  return (uint64_t)((saddr & 0x3FFFF) >> 4) | ((uint64_t)(lbo >> 4) << 16) | ((uint64_t)(sbo >> 4) << 32) | (1ull << 62);
}
__device__ __forceinline__ uint32_t pack_bf16(float lo, float hi) {
  uint32_t r; asm("cvt.rn.bf16x2.f32 %0, %1, %2;" : "=r"(r) : "f"(hi), "f"(lo)); return r;
}
__device__ __forceinline__ float bf_lo(uint32_t v) { return __uint_as_float(v << 16); }
__device__ __forceinline__ float bf_hi(uint32_t v) { return __uint_as_float(v & 0xFFFF0000u); }
__device__ __forceinline__ float rbf(float x) { return __bfloat162float(__float2bfloat16_rn(x)); }
__device__ __forceinline__ float ex2(float x) { float r; asm("ex2.approx.ftz.f32 %0, %1;" : "=f"(r) : "f"(x)); return r; }
__device__ __forceinline__ void red_add_v2(float* p, float a, float b) {
  asm volatile("red.global.add.v2.f32 [%0], {%1, %2};" ::"l"(p), "f"(a), "f"(b) : "memory");
}
__device__ __forceinline__ void pdl_wait() { asm volatile("griddepcontrol.wait;" ::: "memory"); }
__device__ __forceinline__ void pdl_launch() { asm volatile("griddepcontrol.launch_dependents;" ::: "memory"); }

__device__ __forceinline__ void wgmma_m64n256k16_ss_tb(float (&d)[128], uint64_t da, uint64_t db, int sc) {
  asm volatile("{\n.reg .pred p;\nsetp.ne.b32 p, %130, 0;\n"
    "wgmma.mma_async.sync.aligned.m64n256k16.f32.bf16.bf16 {%0, %1, %2, %3, %4, %5, %6, %7, %8, %9, %10, %11, %12, %13, %14, %15, %16, %17, %18, %19, %20, %21, %22, %23, %24, %25, %26, %27, %28, %29, %30, %31, %32, %33, %34, %35, %36, %37, %38, %39, %40, %41, %42, %43, %44, %45, %46, %47, %48, %49, %50, %51, %52, %53, %54, %55, %56, %57, %58, %59, %60, %61, %62, %63, %64, %65, %66, %67, %68, %69, %70, %71, %72, %73, %74, %75, %76, %77, %78, %79, %80, %81, %82, %83, %84, %85, %86, %87, %88, %89, %90, %91, %92, %93, %94, %95, %96, %97, %98, %99, %100, %101, %102, %103, %104, %105, %106, %107, %108, %109, %110, %111, %112, %113, %114, %115, %116, %117, %118, %119, %120, %121, %122, %123, %124, %125, %126, %127}, %128, %129, p, 1, 1, 0, 1;\n}\n"
    : "+f"(d[0]), "+f"(d[1]), "+f"(d[2]), "+f"(d[3]), "+f"(d[4]), "+f"(d[5]), "+f"(d[6]), "+f"(d[7]), "+f"(d[8]), "+f"(d[9]), "+f"(d[10]), "+f"(d[11]), "+f"(d[12]), "+f"(d[13]), "+f"(d[14]), "+f"(d[15]), "+f"(d[16]), "+f"(d[17]), "+f"(d[18]), "+f"(d[19]), "+f"(d[20]), "+f"(d[21]), "+f"(d[22]), "+f"(d[23]), "+f"(d[24]), "+f"(d[25]), "+f"(d[26]), "+f"(d[27]), "+f"(d[28]), "+f"(d[29]), "+f"(d[30]), "+f"(d[31]), "+f"(d[32]), "+f"(d[33]), "+f"(d[34]), "+f"(d[35]), "+f"(d[36]), "+f"(d[37]), "+f"(d[38]), "+f"(d[39]), "+f"(d[40]), "+f"(d[41]), "+f"(d[42]), "+f"(d[43]), "+f"(d[44]), "+f"(d[45]), "+f"(d[46]), "+f"(d[47]), "+f"(d[48]), "+f"(d[49]), "+f"(d[50]), "+f"(d[51]), "+f"(d[52]), "+f"(d[53]), "+f"(d[54]), "+f"(d[55]), "+f"(d[56]), "+f"(d[57]), "+f"(d[58]), "+f"(d[59]), "+f"(d[60]), "+f"(d[61]), "+f"(d[62]), "+f"(d[63]), "+f"(d[64]), "+f"(d[65]), "+f"(d[66]), "+f"(d[67]), "+f"(d[68]), "+f"(d[69]), "+f"(d[70]), "+f"(d[71]), "+f"(d[72]), "+f"(d[73]), "+f"(d[74]), "+f"(d[75]), "+f"(d[76]), "+f"(d[77]), "+f"(d[78]), "+f"(d[79]), "+f"(d[80]), "+f"(d[81]), "+f"(d[82]), "+f"(d[83]), "+f"(d[84]), "+f"(d[85]), "+f"(d[86]), "+f"(d[87]), "+f"(d[88]), "+f"(d[89]), "+f"(d[90]), "+f"(d[91]), "+f"(d[92]), "+f"(d[93]), "+f"(d[94]), "+f"(d[95]), "+f"(d[96]), "+f"(d[97]), "+f"(d[98]), "+f"(d[99]), "+f"(d[100]), "+f"(d[101]), "+f"(d[102]), "+f"(d[103]), "+f"(d[104]), "+f"(d[105]), "+f"(d[106]), "+f"(d[107]), "+f"(d[108]), "+f"(d[109]), "+f"(d[110]), "+f"(d[111]), "+f"(d[112]), "+f"(d[113]), "+f"(d[114]), "+f"(d[115]), "+f"(d[116]), "+f"(d[117]), "+f"(d[118]), "+f"(d[119]), "+f"(d[120]), "+f"(d[121]), "+f"(d[122]), "+f"(d[123]), "+f"(d[124]), "+f"(d[125]), "+f"(d[126]), "+f"(d[127])
    : "l"(da), "l"(db), "r"(sc));
}
__device__ __forceinline__ void wgmma_m64n128k16_ss(float (&d)[64], uint64_t da, uint64_t db, int sc) {
  asm volatile("{\n.reg .pred p;\nsetp.ne.b32 p, %66, 0;\n"
    "wgmma.mma_async.sync.aligned.m64n128k16.f32.bf16.bf16 {%0, %1, %2, %3, %4, %5, %6, %7, %8, %9, %10, %11, %12, %13, %14, %15, %16, %17, %18, %19, %20, %21, %22, %23, %24, %25, %26, %27, %28, %29, %30, %31, %32, %33, %34, %35, %36, %37, %38, %39, %40, %41, %42, %43, %44, %45, %46, %47, %48, %49, %50, %51, %52, %53, %54, %55, %56, %57, %58, %59, %60, %61, %62, %63}, %64, %65, p, 1, 1, 0, 0;\n}\n"
    : "+f"(d[0]), "+f"(d[1]), "+f"(d[2]), "+f"(d[3]), "+f"(d[4]), "+f"(d[5]), "+f"(d[6]), "+f"(d[7]), "+f"(d[8]), "+f"(d[9]), "+f"(d[10]), "+f"(d[11]), "+f"(d[12]), "+f"(d[13]), "+f"(d[14]), "+f"(d[15]), "+f"(d[16]), "+f"(d[17]), "+f"(d[18]), "+f"(d[19]), "+f"(d[20]), "+f"(d[21]), "+f"(d[22]), "+f"(d[23]), "+f"(d[24]), "+f"(d[25]), "+f"(d[26]), "+f"(d[27]), "+f"(d[28]), "+f"(d[29]), "+f"(d[30]), "+f"(d[31]), "+f"(d[32]), "+f"(d[33]), "+f"(d[34]), "+f"(d[35]), "+f"(d[36]), "+f"(d[37]), "+f"(d[38]), "+f"(d[39]), "+f"(d[40]), "+f"(d[41]), "+f"(d[42]), "+f"(d[43]), "+f"(d[44]), "+f"(d[45]), "+f"(d[46]), "+f"(d[47]), "+f"(d[48]), "+f"(d[49]), "+f"(d[50]), "+f"(d[51]), "+f"(d[52]), "+f"(d[53]), "+f"(d[54]), "+f"(d[55]), "+f"(d[56]), "+f"(d[57]), "+f"(d[58]), "+f"(d[59]), "+f"(d[60]), "+f"(d[61]), "+f"(d[62]), "+f"(d[63])
    : "l"(da), "l"(db), "r"(sc));
}
__device__ __forceinline__ void wgmma_m64n256k16_rs_tb(float (&d)[128], uint32_t a0, uint32_t a1, uint32_t a2, uint32_t a3, uint64_t db, int sc) {
  asm volatile("{\n.reg .pred p;\nsetp.ne.b32 p, %133, 0;\n"
    "wgmma.mma_async.sync.aligned.m64n256k16.f32.bf16.bf16 {%0, %1, %2, %3, %4, %5, %6, %7, %8, %9, %10, %11, %12, %13, %14, %15, %16, %17, %18, %19, %20, %21, %22, %23, %24, %25, %26, %27, %28, %29, %30, %31, %32, %33, %34, %35, %36, %37, %38, %39, %40, %41, %42, %43, %44, %45, %46, %47, %48, %49, %50, %51, %52, %53, %54, %55, %56, %57, %58, %59, %60, %61, %62, %63, %64, %65, %66, %67, %68, %69, %70, %71, %72, %73, %74, %75, %76, %77, %78, %79, %80, %81, %82, %83, %84, %85, %86, %87, %88, %89, %90, %91, %92, %93, %94, %95, %96, %97, %98, %99, %100, %101, %102, %103, %104, %105, %106, %107, %108, %109, %110, %111, %112, %113, %114, %115, %116, %117, %118, %119, %120, %121, %122, %123, %124, %125, %126, %127}, {%128, %129, %130, %131}, %132, p, 1, 1, 1;\n}\n"
    : "+f"(d[0]), "+f"(d[1]), "+f"(d[2]), "+f"(d[3]), "+f"(d[4]), "+f"(d[5]), "+f"(d[6]), "+f"(d[7]), "+f"(d[8]), "+f"(d[9]), "+f"(d[10]), "+f"(d[11]), "+f"(d[12]), "+f"(d[13]), "+f"(d[14]), "+f"(d[15]), "+f"(d[16]), "+f"(d[17]), "+f"(d[18]), "+f"(d[19]), "+f"(d[20]), "+f"(d[21]), "+f"(d[22]), "+f"(d[23]), "+f"(d[24]), "+f"(d[25]), "+f"(d[26]), "+f"(d[27]), "+f"(d[28]), "+f"(d[29]), "+f"(d[30]), "+f"(d[31]), "+f"(d[32]), "+f"(d[33]), "+f"(d[34]), "+f"(d[35]), "+f"(d[36]), "+f"(d[37]), "+f"(d[38]), "+f"(d[39]), "+f"(d[40]), "+f"(d[41]), "+f"(d[42]), "+f"(d[43]), "+f"(d[44]), "+f"(d[45]), "+f"(d[46]), "+f"(d[47]), "+f"(d[48]), "+f"(d[49]), "+f"(d[50]), "+f"(d[51]), "+f"(d[52]), "+f"(d[53]), "+f"(d[54]), "+f"(d[55]), "+f"(d[56]), "+f"(d[57]), "+f"(d[58]), "+f"(d[59]), "+f"(d[60]), "+f"(d[61]), "+f"(d[62]), "+f"(d[63]), "+f"(d[64]), "+f"(d[65]), "+f"(d[66]), "+f"(d[67]), "+f"(d[68]), "+f"(d[69]), "+f"(d[70]), "+f"(d[71]), "+f"(d[72]), "+f"(d[73]), "+f"(d[74]), "+f"(d[75]), "+f"(d[76]), "+f"(d[77]), "+f"(d[78]), "+f"(d[79]), "+f"(d[80]), "+f"(d[81]), "+f"(d[82]), "+f"(d[83]), "+f"(d[84]), "+f"(d[85]), "+f"(d[86]), "+f"(d[87]), "+f"(d[88]), "+f"(d[89]), "+f"(d[90]), "+f"(d[91]), "+f"(d[92]), "+f"(d[93]), "+f"(d[94]), "+f"(d[95]), "+f"(d[96]), "+f"(d[97]), "+f"(d[98]), "+f"(d[99]), "+f"(d[100]), "+f"(d[101]), "+f"(d[102]), "+f"(d[103]), "+f"(d[104]), "+f"(d[105]), "+f"(d[106]), "+f"(d[107]), "+f"(d[108]), "+f"(d[109]), "+f"(d[110]), "+f"(d[111]), "+f"(d[112]), "+f"(d[113]), "+f"(d[114]), "+f"(d[115]), "+f"(d[116]), "+f"(d[117]), "+f"(d[118]), "+f"(d[119]), "+f"(d[120]), "+f"(d[121]), "+f"(d[122]), "+f"(d[123]), "+f"(d[124]), "+f"(d[125]), "+f"(d[126]), "+f"(d[127])
    : "r"(a0), "r"(a1), "r"(a2), "r"(a3), "l"(db), "r"(sc));
}
__device__ __forceinline__ void wgmma_m64n128k16_ss_tb(float (&d)[64], uint64_t da, uint64_t db, int sc) {
  asm volatile("{\n.reg .pred p;\nsetp.ne.b32 p, %66, 0;\n"
    "wgmma.mma_async.sync.aligned.m64n128k16.f32.bf16.bf16 {%0, %1, %2, %3, %4, %5, %6, %7, %8, %9, %10, %11, %12, %13, %14, %15, %16, %17, %18, %19, %20, %21, %22, %23, %24, %25, %26, %27, %28, %29, %30, %31, %32, %33, %34, %35, %36, %37, %38, %39, %40, %41, %42, %43, %44, %45, %46, %47, %48, %49, %50, %51, %52, %53, %54, %55, %56, %57, %58, %59, %60, %61, %62, %63}, %64, %65, p, 1, 1, 0, 1;\n}\n"
    : "+f"(d[0]), "+f"(d[1]), "+f"(d[2]), "+f"(d[3]), "+f"(d[4]), "+f"(d[5]), "+f"(d[6]), "+f"(d[7]), "+f"(d[8]), "+f"(d[9]), "+f"(d[10]), "+f"(d[11]), "+f"(d[12]), "+f"(d[13]), "+f"(d[14]), "+f"(d[15]), "+f"(d[16]), "+f"(d[17]), "+f"(d[18]), "+f"(d[19]), "+f"(d[20]), "+f"(d[21]), "+f"(d[22]), "+f"(d[23]), "+f"(d[24]), "+f"(d[25]), "+f"(d[26]), "+f"(d[27]), "+f"(d[28]), "+f"(d[29]), "+f"(d[30]), "+f"(d[31]), "+f"(d[32]), "+f"(d[33]), "+f"(d[34]), "+f"(d[35]), "+f"(d[36]), "+f"(d[37]), "+f"(d[38]), "+f"(d[39]), "+f"(d[40]), "+f"(d[41]), "+f"(d[42]), "+f"(d[43]), "+f"(d[44]), "+f"(d[45]), "+f"(d[46]), "+f"(d[47]), "+f"(d[48]), "+f"(d[49]), "+f"(d[50]), "+f"(d[51]), "+f"(d[52]), "+f"(d[53]), "+f"(d[54]), "+f"(d[55]), "+f"(d[56]), "+f"(d[57]), "+f"(d[58]), "+f"(d[59]), "+f"(d[60]), "+f"(d[61]), "+f"(d[62]), "+f"(d[63])
    : "l"(da), "l"(db), "r"(sc));
}
__device__ __forceinline__ void wgmma_m64n128k16_rs_tb(float (&d)[64], uint32_t a0, uint32_t a1, uint32_t a2, uint32_t a3, uint64_t db, int sc) {
  asm volatile("{\n.reg .pred p;\nsetp.ne.b32 p, %69, 0;\n"
    "wgmma.mma_async.sync.aligned.m64n128k16.f32.bf16.bf16 {%0, %1, %2, %3, %4, %5, %6, %7, %8, %9, %10, %11, %12, %13, %14, %15, %16, %17, %18, %19, %20, %21, %22, %23, %24, %25, %26, %27, %28, %29, %30, %31, %32, %33, %34, %35, %36, %37, %38, %39, %40, %41, %42, %43, %44, %45, %46, %47, %48, %49, %50, %51, %52, %53, %54, %55, %56, %57, %58, %59, %60, %61, %62, %63}, {%64, %65, %66, %67}, %68, p, 1, 1, 1;\n}\n"
    : "+f"(d[0]), "+f"(d[1]), "+f"(d[2]), "+f"(d[3]), "+f"(d[4]), "+f"(d[5]), "+f"(d[6]), "+f"(d[7]), "+f"(d[8]), "+f"(d[9]), "+f"(d[10]), "+f"(d[11]), "+f"(d[12]), "+f"(d[13]), "+f"(d[14]), "+f"(d[15]), "+f"(d[16]), "+f"(d[17]), "+f"(d[18]), "+f"(d[19]), "+f"(d[20]), "+f"(d[21]), "+f"(d[22]), "+f"(d[23]), "+f"(d[24]), "+f"(d[25]), "+f"(d[26]), "+f"(d[27]), "+f"(d[28]), "+f"(d[29]), "+f"(d[30]), "+f"(d[31]), "+f"(d[32]), "+f"(d[33]), "+f"(d[34]), "+f"(d[35]), "+f"(d[36]), "+f"(d[37]), "+f"(d[38]), "+f"(d[39]), "+f"(d[40]), "+f"(d[41]), "+f"(d[42]), "+f"(d[43]), "+f"(d[44]), "+f"(d[45]), "+f"(d[46]), "+f"(d[47]), "+f"(d[48]), "+f"(d[49]), "+f"(d[50]), "+f"(d[51]), "+f"(d[52]), "+f"(d[53]), "+f"(d[54]), "+f"(d[55]), "+f"(d[56]), "+f"(d[57]), "+f"(d[58]), "+f"(d[59]), "+f"(d[60]), "+f"(d[61]), "+f"(d[62]), "+f"(d[63])
    : "r"(a0), "r"(a1), "r"(a2), "r"(a3), "l"(db), "r"(sc));
}
__device__ __forceinline__ void wgmma_m64n64k16_ss_tb(float (&d)[32], uint64_t da, uint64_t db, int sc) {
  asm volatile("{\n.reg .pred p;\nsetp.ne.b32 p, %34, 0;\n"
    "wgmma.mma_async.sync.aligned.m64n64k16.f32.bf16.bf16 {%0, %1, %2, %3, %4, %5, %6, %7, %8, %9, %10, %11, %12, %13, %14, %15, %16, %17, %18, %19, %20, %21, %22, %23, %24, %25, %26, %27, %28, %29, %30, %31}, %32, %33, p, 1, 1, 0, 1;\n}\n"
    : "+f"(d[0]), "+f"(d[1]), "+f"(d[2]), "+f"(d[3]), "+f"(d[4]), "+f"(d[5]), "+f"(d[6]), "+f"(d[7]), "+f"(d[8]), "+f"(d[9]), "+f"(d[10]), "+f"(d[11]), "+f"(d[12]), "+f"(d[13]), "+f"(d[14]), "+f"(d[15]), "+f"(d[16]), "+f"(d[17]), "+f"(d[18]), "+f"(d[19]), "+f"(d[20]), "+f"(d[21]), "+f"(d[22]), "+f"(d[23]), "+f"(d[24]), "+f"(d[25]), "+f"(d[26]), "+f"(d[27]), "+f"(d[28]), "+f"(d[29]), "+f"(d[30]), "+f"(d[31])
    : "l"(da), "l"(db), "r"(sc));
}
__device__ __forceinline__ void wgmma_m64n64k16_rs_tb(float (&d)[32], uint32_t a0, uint32_t a1, uint32_t a2, uint32_t a3, uint64_t db, int sc) {
  asm volatile("{\n.reg .pred p;\nsetp.ne.b32 p, %37, 0;\n"
    "wgmma.mma_async.sync.aligned.m64n64k16.f32.bf16.bf16 {%0, %1, %2, %3, %4, %5, %6, %7, %8, %9, %10, %11, %12, %13, %14, %15, %16, %17, %18, %19, %20, %21, %22, %23, %24, %25, %26, %27, %28, %29, %30, %31}, {%32, %33, %34, %35}, %36, p, 1, 1, 1;\n}\n"
    : "+f"(d[0]), "+f"(d[1]), "+f"(d[2]), "+f"(d[3]), "+f"(d[4]), "+f"(d[5]), "+f"(d[6]), "+f"(d[7]), "+f"(d[8]), "+f"(d[9]), "+f"(d[10]), "+f"(d[11]), "+f"(d[12]), "+f"(d[13]), "+f"(d[14]), "+f"(d[15]), "+f"(d[16]), "+f"(d[17]), "+f"(d[18]), "+f"(d[19]), "+f"(d[20]), "+f"(d[21]), "+f"(d[22]), "+f"(d[23]), "+f"(d[24]), "+f"(d[25]), "+f"(d[26]), "+f"(d[27]), "+f"(d[28]), "+f"(d[29]), "+f"(d[30]), "+f"(d[31])
    : "r"(a0), "r"(a1), "r"(a2), "r"(a3), "l"(db), "r"(sc));
}

#define TM(id)
#define GT_MIN(i)
#define GT_MAX(i)

constexpr int NS = 5;
constexpr uint32_t STG = 32768;
constexpr uint32_t SM_Q = 0;
constexpr uint32_t SM_RING = 65536;
constexpr uint32_t SM_BAR = SM_RING + NS * STG;
constexpr uint32_t SM_TOTAL = SM_BAR + 256 + 1024;

struct Ring {
  uint32_t base, full0, empty0; int it;
  __device__ __forceinline__ uint32_t stage() const { return (uint32_t)(it % NS); }
  __device__ __forceinline__ uint32_t phase() const { return (uint32_t)((it / NS) & 1); }
  __device__ __forceinline__ uint32_t buf() const { return base + stage() * STG; }
  __device__ __forceinline__ uint32_t full() const { return full0 + stage() * 8; }
  __device__ __forceinline__ uint32_t empty() const { return empty0 + stage() * 8; }
  __device__ __forceinline__ uint32_t acquire(uint32_t bytes) {
    mbar_wait(empty(), phase() ^ 1); mbar_expect_tx(full(), bytes); return buf();
  }
  __device__ __forceinline__ uint32_t wait() { mbar_wait(full(), phase()); return buf(); }
};
__device__ __forceinline__ void ring_release(uint32_t empty_bar, int lane) {
  __syncwarp();
  if (lane < 2) mbar_arrive_remote(empty_bar, (uint32_t)lane);
}

__device__ __forceinline__ void gemm_k448_n256(Ring& r, float (&acc)[128], int wg, int lane) {
  uint32_t hb = 0, hrel = 0, prel = 0, phrel = 0;
#pragma unroll
  for (int c = 0; c < 7; ++c) {
    if ((c & 1) == 0) { hb = r.wait(); hrel = r.empty(); r.it++; }
    uint32_t wb = r.wait(); uint32_t wrel = r.empty(); r.it++;
    uint64_t da = mk_desc(hb + (c & 1) * 16384 + wg * 8192, 16, 1024);
    uint64_t db = mk_desc(wb, 8192, 1024);
    wg_fence();
#pragma unroll
    for (int k = 0; k < 4; ++k) wgmma_m64n256k16_ss_tb(acc, da + k * 2, db + k * 128, (c | k) != 0);
    wg_commit();
    if (c > 0) {
      wg_wait<1>();
      ring_release(prel, lane);
      if ((c & 1) == 0) ring_release(phrel, lane);
    }
    prel = wrel; phrel = hrel;
  }
  wg_wait<0>();
  ring_release(prel, lane); ring_release(phrel, lane);
}

template <bool RELU>
__device__ __forceinline__ void store_tile_bf16(uint32_t base, const float (&acc)[128], int rloc, int t4) {
  uint32_t row0 = base + rloc * 128, row1 = row0 + 8 * 128;
  uint32_t sw = (uint32_t)(rloc & 7);
#pragma unroll
  for (int j = 0; j < 32; ++j) {
    uint32_t off = (uint32_t)(j >> 3) * 16384 + ((((uint32_t)j & 7) ^ sw) << 4) + t4 * 4;
    float a = acc[4 * j], b = acc[4 * j + 1], c = acc[4 * j + 2], d = acc[4 * j + 3];
    if (RELU) { a = fmaxf(a, 0.f); b = fmaxf(b, 0.f); c = fmaxf(c, 0.f); d = fmaxf(d, 0.f); }
    asm volatile("st.shared.b32 [%0], %1;" ::"r"(row0 + off), "r"(pack_bf16(a, b)) : "memory");
    asm volatile("st.shared.b32 [%0], %1;" ::"r"(row1 + off), "r"(pack_bf16(c, d)) : "memory");
  }
}

template <int NSM, int NRG>
__device__ __forceinline__ void out_proj(Ring& r, const uint32_t (&ob)[64], uint32_t abase,
                                         float* dst, int lane, int t4) {
  constexpr int NST = (NSM + NRG) / 2;
  constexpr int RPS = 16 / NST;
  uint32_t prel = 0;
  float accA[64], accB[64];
  float(&cur32)[32] = *reinterpret_cast<float(*)[32]>(&accB[0]);
#pragma unroll
  for (int pass = 0; pass < 4; ++pass) {
    float(&cur)[64] = (pass & 1) ? accB : accA;
    float(&prv)[64] = (pass & 1) ? accA : accB;
#pragma unroll
    for (int st = 0; st < NST; ++st) {
      uint32_t wb = r.wait(); uint32_t rel = r.empty(); r.it++;
      wg_fence();
#pragma unroll
      for (int cc = 0; cc < 2; ++cc) {
        const int c = 2 * st + cc;
#pragma unroll
        for (int k = 0; k < 4; ++k) {
          const int sc = (c | k) != 0;
          if (pass < 3) {
            uint64_t db = mk_desc(wb + cc * 16384 + k * 2048, 8192, 1024);
            if (c < NSM) wgmma_m64n128k16_ss_tb(cur, mk_desc(abase + c * 16384 + k * 32, 16, 1024), db, sc);
            else { const int o = (c - NSM) * 16 + 4 * k; wgmma_m64n128k16_rs_tb(cur, ob[o], ob[o + 1], ob[o + 2], ob[o + 3], db, sc); }
          } else {
            uint64_t db = mk_desc(wb + cc * 8192 + k * 2048, 8192, 1024);
            if (c < NSM) wgmma_m64n64k16_ss_tb(cur32, mk_desc(abase + c * 16384 + k * 32, 16, 1024), db, sc);
            else { const int o = (c - NSM) * 16 + 4 * k; wgmma_m64n64k16_rs_tb(cur32, ob[o], ob[o + 1], ob[o + 2], ob[o + 3], db, sc); }
          }
        }
      }
      wg_commit();
      if (pass | st) { wg_wait<1>(); ring_release(prel, lane); }
      prel = rel;
      if (pass > 0) {
#pragma unroll
        for (int j = st * RPS; j < (st + 1) * RPS; ++j) {
          float* d = dst + (pass - 1) * 128 + 8 * j + 2 * t4;
          red_add_v2(d, prv[4 * j], prv[4 * j + 1]);
          red_add_v2(d + 8 * DM, prv[4 * j + 2], prv[4 * j + 3]);
        }
      }
    }
  }
  wg_wait<0>(); ring_release(prel, lane);
#pragma unroll
  for (int j = 0; j < 8; ++j) {
    float* d = dst + 384 + 8 * j + 2 * t4;
    red_add_v2(d, cur32[4 * j], cur32[4 * j + 1]);
    red_add_v2(d + 8 * DM, cur32[4 * j + 2], cur32[4 * j + 3]);
  }
}
__device__ __forceinline__ void out_proj_loads(Ring& r, const CUtensorMap* tm, int krow0, int nch, uint32_t rank) {
  for (int pass = 0; pass < 4; ++pass)
    for (int st = 0; st < nch / 2; ++st) {
      if (pass < 3) {
        uint32_t b = r.acquire(32768);
        for (int x = 0; x < 2; ++x)
          tma_load_mc(b + rank * 16384 + x * 8192, tm, pass * 128 + x * 64, krow0 + (2 * st + rank) * 64, r.full(), 3);
      } else {
        uint32_t b = r.acquire(16384);
        tma_load_mc(b + rank * 8192, tm, 384, krow0 + (2 * st + rank) * 64, r.full(), 3);
      }
      r.it++;
    }
}

__global__ void __cluster_dims__(2, 1, 1) __launch_bounds__(384, 1)
attn_kernel(const __grid_constant__ CUtensorMap tm_h, const __grid_constant__ CUtensorMap tm_wq,
            const __grid_constant__ CUtensorMap tm_k, const __grid_constant__ CUtensorMap tm_v,
            const __grid_constant__ CUtensorMap tm_wo, const __grid_constant__ CUtensorMap tm_oA) {
  extern __shared__ uint8_t smem_raw[];
  const uint32_t sb = (smem_u32(smem_raw) + 1023) & ~1023u;
  const int tid = threadIdx.x, wg = tid >> 7, lane = tid & 31;
  const int qt = blockIdx.x, kvh = blockIdx.y;
  const uint32_t rank = cluster_rank();
  Ring r; r.base = sb + SM_RING; r.full0 = sb + SM_BAR; r.empty0 = sb + SM_BAR + 64; r.it = 0;
  const uint32_t bar_oA = sb + SM_BAR + 128, bar_oAf = sb + SM_BAR + 136;
  if (tid == 0) {
    for (int i = 0; i < NS; ++i) { mbar_init(r.full0 + 8 * i, 1); mbar_init(r.empty0 + 8 * i, 16); }
    mbar_init(bar_oA, 256); mbar_init(bar_oAf, 1);
    asm volatile("fence.mbarrier_init.release.cluster;" ::: "memory");
  }
  cluster_sync_all();
  pdl_wait();
  GT_MIN(4);

  if (wg == 2) {
    asm volatile("setmaxnreg.dec.sync.aligned.u32 24;");
    if (tid == 256) {
      const int krow0 = kvh * SKV + (SKV - WIN);
      for (int hh = 0; hh < 2; ++hh) {
        const int head = kvh * 2 + hh;
        for (int p = 0; p < 4; ++p) {
          int nc = (p < 3) ? 2 : 1;
          uint32_t b = r.acquire(nc * 16384);
          for (int c = 0; c < nc; ++c) tma_load(b + c * 16384, &tm_h, (2 * p + c) * 64, qt * 128, r.full());
          r.it++;
          for (int c = 0; c < nc; ++c) {
            b = r.acquire(32768);
            for (int x = 0; x < 2; ++x) {
              int bx = rank * 2 + x;
              tma_load_mc(b + bx * 8192, &tm_wq, head * 256 + bx * 64, (2 * p + c) * 64, r.full(), 3);
            }
            r.it++;
          }
        }
        for (int t = 0; t < 4; ++t) {
          for (int hf = 0; hf < 2; ++hf) {
            uint32_t b = r.acquire(32768);
            tma_load_mc(b + rank * 16384, &tm_k, (2 * hf + rank) * 64, krow0 + t * 128, r.full(), 3);
            r.it++;
          }
          for (int hf = 0; hf < 2; ++hf) {
            uint32_t b = r.acquire(32768);
            for (int x = 0; x < 2; ++x) {
              int bx = rank * 2 + x;
              tma_load_mc(b + bx * 8192, &tm_v, bx * 64, krow0 + t * 128 + hf * 64, r.full(), 3);
            }
            r.it++;
          }
        }
      }
      mbar_wait(bar_oA, 0);
      mbar_expect_tx(bar_oAf, 65536);
      for (int c = 0; c < 4; ++c) tma_load(sb + SM_Q + c * 16384, &tm_oA, c * 64, kvh * SEQ + qt * 128, bar_oAf);
      out_proj_loads(r, &tm_wo, kvh * 512, 8, rank);
    }
  } else {
    asm volatile("setmaxnreg.inc.sync.aligned.u32 240;");
    const int warp = (tid >> 5) & 3, g = lane >> 2, t4 = lane & 3;
    const int rloc = wg * 64 + warp * 16 + g;
    uint32_t ob[64];
    float acc[128];
    const float CS = 1.4426950408889634f * 0.0625f;
    TM(0);
#pragma unroll 1
    for (int hh = 0; hh < 2; ++hh) {
      gemm_k448_n256(r, acc, wg, lane);
      TM(1);
      store_tile_bf16<false>(sb + SM_Q, acc, rloc, t4);
      fence_async_smem();
      if (hh == 1) fence_async();
      bar_sync(1 + wg, 128);
      float m0 = -INFINITY, m1 = -INFINITY, l0 = 0.f, l1 = 0.f;
      const uint32_t qa0 = sb + SM_Q + wg * 8192;
      if (wg == 1) bar_arrive(3, 256);
      TM(2);
      bar_sync(3 + wg, 256);
#pragma unroll 1
      for (int t = 0; t < 4; ++t) {
        float s[64];
        TM(3);
        {
          uint32_t qa = qa0; asm volatile("" : "+r"(qa));
          uint32_t ka = r.wait(); uint32_t rel0 = r.empty(); r.it++;
          wg_fence();
#pragma unroll
          for (int k = 0; k < 8; ++k)
            wgmma_m64n128k16_ss(s, mk_desc(qa + (k >> 2) * 16384 + (k & 3) * 32, 16, 1024),
                                mk_desc(ka + (k >> 2) * 16384 + (k & 3) * 32, 16, 1024), k != 0);
          wg_commit();
          uint32_t kb = r.wait(); uint32_t rel1 = r.empty(); r.it++;
          wg_fence();
#pragma unroll
          for (int k = 0; k < 8; ++k)
            wgmma_m64n128k16_ss(s, mk_desc(qa + (2 + (k >> 2)) * 16384 + (k & 3) * 32, 16, 1024),
                                mk_desc(kb + (k >> 2) * 16384 + (k & 3) * 32, 16, 1024), 1);
          wg_commit();
          bar_arrive(4 - wg, 256);
          wg_wait<1>(); ring_release(rel0, lane);
          wg_wait<0>(); ring_release(rel1, lane);
        }
        TM(4);
        float mx0 = m0, mx1 = m1;
#pragma unroll
        for (int j = 0; j < 16; ++j) {
          uint32_t a = pack_bf16(s[4 * j], s[4 * j + 1]), b = pack_bf16(s[4 * j + 2], s[4 * j + 3]);
          s[4 * j] = bf_lo(a); s[4 * j + 1] = bf_hi(a); s[4 * j + 2] = bf_lo(b); s[4 * j + 3] = bf_hi(b);
          mx0 = fmaxf(mx0, fmaxf(s[4 * j], s[4 * j + 1])); mx1 = fmaxf(mx1, fmaxf(s[4 * j + 2], s[4 * j + 3]));
        }
        mx0 = fmaxf(mx0, __shfl_xor_sync(0xffffffffu, mx0, 1)); mx0 = fmaxf(mx0, __shfl_xor_sync(0xffffffffu, mx0, 2));
        mx1 = fmaxf(mx1, __shfl_xor_sync(0xffffffffu, mx1, 1)); mx1 = fmaxf(mx1, __shfl_xor_sync(0xffffffffu, mx1, 2));
        const float c0 = ex2((m0 - mx0) * CS), c1 = ex2((m1 - mx1) * CS);
        m0 = mx0; m1 = mx1;
        const float nb0 = -mx0 * CS, nb1 = -mx1 * CS;
        float ps0 = 0.f, ps1 = 0.f;
        uint32_t pa[32];
#pragma unroll
        for (int j = 0; j < 16; ++j) {
          float e0 = ex2(fmaf(s[4 * j], CS, nb0)), e1 = ex2(fmaf(s[4 * j + 1], CS, nb0));
          float e2 = ex2(fmaf(s[4 * j + 2], CS, nb1)), e3 = ex2(fmaf(s[4 * j + 3], CS, nb1));
          ps0 += e0 + e1; ps1 += e2 + e3;
          pa[2 * j] = pack_bf16(e0, e1); pa[2 * j + 1] = pack_bf16(e2, e3);
        }
        l0 = l0 * c0 + ps0; l1 = l1 * c1 + ps1;
        if (t > 0) {
#pragma unroll
          for (int j = 0; j < 32; ++j) { acc[4 * j] *= c0; acc[4 * j + 1] *= c0; acc[4 * j + 2] *= c1; acc[4 * j + 3] *= c1; }
        }
#pragma unroll
        for (int j = 0; j < 32; ++j) asm volatile("" : "+r"(pa[j]));
#pragma unroll
        for (int j = 0; j < 128; ++j) asm volatile("" : "+f"(acc[j]));
        asm volatile("" : "+f"(l0), "+f"(l1));
        TM(5);
        bar_sync(3 + wg, 256);
        TM(6);
        {
          uint32_t va = r.wait(); uint32_t rel0 = r.empty(); r.it++;
          wg_fence();
#pragma unroll
          for (int k = 0; k < 4; ++k)
            wgmma_m64n256k16_rs_tb(acc, pa[4 * k], pa[4 * k + 1], pa[4 * k + 2], pa[4 * k + 3],
                                   mk_desc(va + k * 2048, 8192, 1024), (t | k) != 0);
          wg_commit();
          uint32_t vb = r.wait(); uint32_t rel1 = r.empty(); r.it++;
          wg_fence();
#pragma unroll
          for (int k = 0; k < 4; ++k)
            wgmma_m64n256k16_rs_tb(acc, pa[16 + 4 * k], pa[16 + 4 * k + 1], pa[16 + 4 * k + 2], pa[16 + 4 * k + 3],
                                   mk_desc(vb + k * 2048, 8192, 1024), 1);
          wg_commit();
          if (t == 3 && wg == 0) bar_arrive(4, 256);
          wg_wait<1>(); ring_release(rel0, lane);
          wg_wait<0>(); ring_release(rel1, lane);
        }
      }
      TM(7);
      l0 += __shfl_xor_sync(0xffffffffu, l0, 1); l0 += __shfl_xor_sync(0xffffffffu, l0, 2);
      l1 += __shfl_xor_sync(0xffffffffu, l1, 1); l1 += __shfl_xor_sync(0xffffffffu, l1, 2);
      const float i0 = 1.f / l0, i1 = 1.f / l1;
#pragma unroll
      for (int j = 0; j < 32; ++j) {
        ob[2 * j] = pack_bf16(acc[4 * j] * i0, acc[4 * j + 1] * i0);
        ob[2 * j + 1] = pack_bf16(acc[4 * j + 2] * i1, acc[4 * j + 3] * i1);
      }
      if (hh == 0) {
        uint32_t* o0 = reinterpret_cast<uint32_t*>(g_oA + ((size_t)kvh * SEQ + qt * 128 + rloc) * DH) + t4;
#pragma unroll
        for (int j = 0; j < 32; ++j) { o0[4 * j] = ob[2 * j]; o0[4 * j + 8 * DH / 2] = ob[2 * j + 1]; }
      }
    }
    mbar_arrive(bar_oA);
    mbar_wait(bar_oAf, 0);
    TM(8);
    out_proj<4, 4>(r, ob, sb + SM_Q + wg * 8192, g_acc1 + (size_t)(qt * 128 + rloc) * DM, lane, t4);
    TM(9);
  }
  cluster_sync_all();
  GT_MAX(5);
}

__global__ void __cluster_dims__(2, 1, 1) __launch_bounds__(384, 1)
ffn_kernel(const __grid_constant__ CUtensorMap tm_h2, const __grid_constant__ CUtensorMap tm_w1,
           const __grid_constant__ CUtensorMap tm_w2) {
  extern __shared__ uint8_t smem_raw[];
  const uint32_t sb = (smem_u32(smem_raw) + 1023) & ~1023u;
  const int tid = threadIdx.x, wg = tid >> 7, lane = tid & 31;
  const int rt = blockIdx.x, sl = blockIdx.y;
  const uint32_t rank = cluster_rank();
  Ring r; r.base = sb + SM_RING; r.full0 = sb + SM_BAR; r.empty0 = sb + SM_BAR + 64; r.it = 0;
  if (tid == 0) {
    for (int i = 0; i < NS; ++i) { mbar_init(r.full0 + 8 * i, 1); mbar_init(r.empty0 + 8 * i, 16); }
    asm volatile("fence.mbarrier_init.release.cluster;" ::: "memory");
  }
  cluster_sync_all();
  pdl_wait();
  GT_MIN(8);
  if (wg == 2) {
    asm volatile("setmaxnreg.dec.sync.aligned.u32 24;");
    if (tid == 256) {
      for (int p = 0; p < 4; ++p) {
        int nc = (p < 3) ? 2 : 1;
        uint32_t b = r.acquire(nc * 16384);
        for (int c = 0; c < nc; ++c) tma_load(b + c * 16384, &tm_h2, (2 * p + c) * 64, rt * 128, r.full());
        r.it++;
        for (int c = 0; c < nc; ++c) {
          b = r.acquire(32768);
          for (int x = 0; x < 2; ++x) {
            int bx = rank * 2 + x;
            tma_load_mc(b + bx * 8192, &tm_w1, sl * 256 + bx * 64, (2 * p + c) * 64, r.full(), 3);
          }
          r.it++;
        }
      }
      out_proj_loads(r, &tm_w2, sl * 256, 4, rank);
    }
  } else {
    asm volatile("setmaxnreg.inc.sync.aligned.u32 240;");
    const int warp = (tid >> 5) & 3, g = lane >> 2, t4 = lane & 3;
    const int rloc = wg * 64 + warp * 16 + g;
    uint32_t ob[64];
    {
      float acc[128];
      TM(20);
      gemm_k448_n256(r, acc, wg, lane);
      TM(21);
      store_tile_bf16<true>(sb + SM_Q, acc, rloc, t4);
    }
    fence_async_smem();
    bar_sync(1 + wg, 128);
    TM(22);
    out_proj<4, 0>(r, ob, sb + SM_Q + wg * 8192, g_acc2 + (size_t)(rt * 128 + rloc) * DM, lane, t4);
    TM(23);
  }
  cluster_sync_all();
  GT_MAX(9);
}

__global__ void __launch_bounds__(512) mod_kernel(const __nv_bfloat16* __restrict__ c, const __nv_bfloat16* __restrict__ wm) {
  __shared__ float red[32][33];
  const int tid = threadIdx.x;
  GT_MIN(0);
  if (blockIdx.x < 84) {
    const int cl = tid & 15, kg = tid >> 4;
    const int col = blockIdx.x * 32 + cl * 2;
    uint32_t v[14];
#pragma unroll
    for (int i = 0; i < 14; ++i) v[i] = *reinterpret_cast<const uint32_t*>(wm + (size_t)(kg * 14 + i) * (6 * DM) + col);
    float a0 = 0.f, a1 = 0.f;
#pragma unroll
    for (int i = 0; i < 14; ++i) {
      float cv = __bfloat162float(c[kg * 14 + i]);
      float sv = rbf(cv / (1.f + __expf(-cv)));
      a0 = fmaf(sv, bf_lo(v[i]), a0); a1 = fmaf(sv, bf_hi(v[i]), a1);
    }
    red[kg][cl * 2] = a0; red[kg][cl * 2 + 1] = a1;
    __syncthreads();
    if (tid < 32) {
      float s = 0.f;
#pragma unroll
      for (int i = 0; i < 32; ++i) s += red[i][tid];
      g_mod[blockIdx.x * 32 + tid] = rbf(s);
    }
  } else {
    float4 z = make_float4(0.f, 0.f, 0.f, 0.f);
    const int n4 = SEQ * DM / 4;
    for (int i = (blockIdx.x - 84) * 512 + tid; i < n4; i += (gridDim.x - 84) * 512) {
      reinterpret_cast<float4*>(g_acc1)[i] = z; reinterpret_cast<float4*>(g_acc2)[i] = z;
    }
  }
  if (blockIdx.x < 84) GT_MAX(1); else GT_MAX(13);
  pdl_launch();
}

__device__ __forceinline__ void ln_row(const float (&x)[14], const float* __restrict__ shift, const float* __restrict__ scale,
                                       __nv_bfloat16* __restrict__ out, int lane) {
  float2 sc[7], sh[7];
#pragma unroll
  for (int i = 0; i < 7; ++i) {
    sc[i] = *reinterpret_cast<const float2*>(scale + i * 64 + lane * 2);
    sh[i] = *reinterpret_cast<const float2*>(shift + i * 64 + lane * 2);
  }
  float s = 0.f;
#pragma unroll
  for (int i = 0; i < 14; ++i) s += x[i];
#pragma unroll
  for (int o = 16; o; o >>= 1) s += __shfl_xor_sync(0xffffffffu, s, o);
  const float mean = s * (1.f / DM);
  float q = 0.f;
#pragma unroll
  for (int i = 0; i < 14; ++i) { float d = x[i] - mean; q = fmaf(d, d, q); }
#pragma unroll
  for (int o = 16; o; o >>= 1) q += __shfl_xor_sync(0xffffffffu, q, o);
  const float mb = rbf(mean), vb = rbf(q * (1.f / DM));
  const float den = rbf(sqrtf(rbf(vb + 1e-5f)));
#pragma unroll
  for (int i = 0; i < 7; ++i) {
    int col = i * 64 + lane * 2;
    float y0 = rbf(rbf(x[2 * i] - mb) / den), y1 = rbf(rbf(x[2 * i + 1] - mb) / den);
    y0 = rbf(y0 * rbf(1.f + sc[i].x)); y1 = rbf(y1 * rbf(1.f + sc[i].y));
    *reinterpret_cast<uint32_t*>(out + col) = pack_bf16(y0 + sh[i].x, y1 + sh[i].y);
  }
}

__global__ void __launch_bounds__(256) ln1_kernel(const __nv_bfloat16* __restrict__ x) {
  const int lane = threadIdx.x & 31, row = blockIdx.x * 8 + (threadIdx.x >> 5);
  float v[14];
#pragma unroll
  for (int i = 0; i < 7; ++i) {
    uint32_t u = *reinterpret_cast<const uint32_t*>(x + (size_t)row * DM + i * 64 + lane * 2);
    v[2 * i] = bf_lo(u); v[2 * i + 1] = bf_hi(u);
  }
  pdl_wait();
  GT_MIN(2);
  ln_row(v, g_mod + 0 * DM, g_mod + 1 * DM, g_h + (size_t)row * DM, lane);
  GT_MAX(3);
  pdl_launch();
}

__global__ void __launch_bounds__(256) ln2_kernel(const __nv_bfloat16* __restrict__ x) {
  const int lane = threadIdx.x & 31, row = blockIdx.x * 8 + (threadIdx.x >> 5);
  float v[14];
  uint32_t xu[7];
#pragma unroll
  for (int i = 0; i < 7; ++i) xu[i] = *reinterpret_cast<const uint32_t*>(x + (size_t)row * DM + i * 64 + lane * 2);
  pdl_wait();
  GT_MIN(6);
  float2 av[7], gv[7];
#pragma unroll
  for (int i = 0; i < 7; ++i) {
    av[i] = *reinterpret_cast<const float2*>(g_acc1 + (size_t)row * DM + i * 64 + lane * 2);
    gv[i] = *reinterpret_cast<const float2*>(g_mod + 2 * DM + i * 64 + lane * 2);
  }
#pragma unroll
  for (int i = 0; i < 7; ++i) {
    int col = i * 64 + lane * 2;
    uint32_t u = xu[i];
    float t0 = rbf(gv[i].x * rbf(av[i].x)), t1 = rbf(gv[i].y * rbf(av[i].y));
    v[2 * i] = rbf(bf_lo(u) + t0); v[2 * i + 1] = rbf(bf_hi(u) + t1);
    *reinterpret_cast<uint32_t*>(g_x1 + (size_t)row * DM + col) = pack_bf16(v[2 * i], v[2 * i + 1]);
  }
  ln_row(v, g_mod + 3 * DM, g_mod + 4 * DM, g_h2 + (size_t)row * DM, lane);
  GT_MAX(7);
  pdl_launch();
}

__global__ void __launch_bounds__(256) final_kernel(__nv_bfloat16* __restrict__ out) {
  pdl_wait();
  GT_MIN(10);
  const int i = blockIdx.x * 256 + threadIdx.x;
  const int col = (i * 2) % DM;
  uint32_t u = reinterpret_cast<const uint32_t*>(g_x1)[i];
  float2 a = reinterpret_cast<const float2*>(g_acc2)[i];
  float t0 = rbf(g_mod[5 * DM + col] * rbf(a.x)), t1 = rbf(g_mod[5 * DM + col + 1] * rbf(a.y));
  reinterpret_cast<uint32_t*>(out)[i] = pack_bf16(bf_lo(u) + t0, bf_hi(u) + t1);
  GT_MAX(11);
}

typedef CUresult (*EncodeFn)(CUtensorMap*, CUtensorMapDataType, cuuint32_t, void*, const cuuint64_t*, const cuuint64_t*,
                             const cuuint32_t*, const cuuint32_t*, CUtensorMapInterleave, CUtensorMapSwizzle,
                             CUtensorMapL2promotion, CUtensorMapFloatOOBfill);

static CUtensorMap make_map(EncodeFn enc, const void* ptr, uint64_t cols, uint64_t rows, uint32_t bx, uint32_t by) {
  CUtensorMap m;
  cuuint64_t dims[2] = {cols, rows};
  cuuint64_t strides[1] = {cols * 2};
  cuuint32_t box[2] = {bx, by};
  cuuint32_t es[2] = {1, 1};
  enc(&m, CU_TENSOR_MAP_DATA_TYPE_BFLOAT16, 2, const_cast<void*>(ptr), dims, strides, box, es, CU_TENSOR_MAP_INTERLEAVE_NONE,
      CU_TENSOR_MAP_SWIZZLE_128B, CU_TENSOR_MAP_L2_PROMOTION_L2_256B, CU_TENSOR_MAP_FLOAT_OOB_FILL_NONE);
  return m;
}

template <typename... Args>
static void launch(void (*k)(Args...), dim3 grid, dim3 block, size_t smem, bool pdl, Args... args) {
  cudaLaunchConfig_t cfg = {};
  cfg.gridDim = grid; cfg.blockDim = block; cfg.dynamicSmemBytes = smem; cfg.stream = cudaStreamPerThread;
  cudaLaunchAttribute at[1];
  at[0].id = cudaLaunchAttributeProgrammaticStreamSerialization; at[0].val.programmaticStreamSerializationAllowed = 1;
  cfg.attrs = at; cfg.numAttrs = pdl ? 1 : 0;
  cudaLaunchKernelEx(&cfg, k, args...);
}

extern "C" void kernel_launch(void* const* d_in, const int* in_sizes, int n_in, void* d_out, int out_size) {
  const __nv_bfloat16* x = (const __nv_bfloat16*)d_in[0];
  const void* kc = d_in[1]; const void* vc = d_in[2]; const void* wq = d_in[3]; const void* wo = d_in[4];
  const void* w1 = d_in[6]; const void* w2 = d_in[7];
  const __nv_bfloat16* c = (const __nv_bfloat16*)d_in[8];
  const __nv_bfloat16* wm = (const __nv_bfloat16*)d_in[9];

  void* fn = nullptr; cudaDriverEntryPointQueryResult qr;
  cudaGetDriverEntryPoint("cuTensorMapEncodeTiled", &fn, cudaEnableDefault, &qr);
  EncodeFn enc = (EncodeFn)fn;
  void *p_h, *p_oA, *p_h2;
  cudaGetSymbolAddress(&p_h, g_h); cudaGetSymbolAddress(&p_oA, g_oA); cudaGetSymbolAddress(&p_h2, g_h2);
  CUtensorMap tm_h = make_map(enc, p_h, DM, SEQ, 64, 128);
  CUtensorMap tm_wq = make_map(enc, wq, 4096, DM, 64, 64);
  CUtensorMap tm_k = make_map(enc, kc, DH, HKV * SKV, 64, 128);
  CUtensorMap tm_v = make_map(enc, vc, DH, HKV * SKV, 64, 64);
  CUtensorMap tm_wo = make_map(enc, wo, DM, 4096, 64, 64);
  CUtensorMap tm_oA = make_map(enc, p_oA, DH, HKV * SEQ, 64, 128);
  CUtensorMap tm_h2 = make_map(enc, p_h2, DM, SEQ, 64, 128);
  CUtensorMap tm_w1 = make_map(enc, w1, DFF, DM, 64, 64);
  CUtensorMap tm_w2 = make_map(enc, w2, DM, DFF, 64, 64);
  cudaFuncSetAttribute(attn_kernel, cudaFuncAttributeMaxDynamicSharedMemorySize, SM_TOTAL);
  cudaFuncSetAttribute(ffn_kernel, cudaFuncAttributeMaxDynamicSharedMemorySize, SM_TOTAL);

  launch(mod_kernel, dim3(84 + 90), dim3(512), 0, false, c, wm);
  launch(ln1_kernel, dim3(SEQ / 8), dim3(256), 0, true, x);
  launch(attn_kernel, dim3(16, 8), dim3(384), SM_TOTAL, true, tm_h, tm_wq, tm_k, tm_v, tm_wo, tm_oA);
  launch(ln2_kernel, dim3(SEQ / 8), dim3(256), 0, true, x);
  launch(ffn_kernel, dim3(16, 7), dim3(384), SM_TOTAL, true, tm_h2, tm_w1, tm_w2);
  launch(final_kernel, dim3(SEQ * DM / 512), dim3(256), 0, true, (__nv_bfloat16*)d_out);
}
```

```cpp
#include <cuda_runtime.h>
#include <cuda_bf16.h>
#include <cuda.h>
#include <stdint.h>

constexpr int SEQ = 2048, DM = 448, HKV = 8, SKV = 2048, DH = 256, WIN = 512, DFF = 1792;

__device__ __align__(1024) float          g_mod[6 * DM];
__device__ __align__(1024) __nv_bfloat16  g_h[SEQ * DM];
__device__ __align__(1024) __nv_bfloat16  g_oA[HKV * SEQ * DH];
__device__ __align__(1024) float          g_acc1[SEQ * DM];
__device__ __align__(1024) float          g_acc2[SEQ * DM];
__device__ __align__(1024) __nv_bfloat16  g_x1[SEQ * DM];
__device__ __align__(1024) __nv_bfloat16  g_h2[SEQ * DM];

__device__ __forceinline__ uint32_t smem_u32(const void* p) { return (uint32_t)__cvta_generic_to_shared(p); }
__device__ __forceinline__ void mbar_init(uint32_t bar, uint32_t cnt) {
  asm volatile("mbarrier.init.shared::cta.b64 [%0], %1;" ::"r"(bar), "r"(cnt));
}
__device__ __forceinline__ void mbar_expect_tx(uint32_t bar, uint32_t bytes) {
  asm volatile("mbarrier.arrive.expect_tx.shared::cta.b64 _, [%0], %1;" ::"r"(bar), "r"(bytes) : "memory");
}
__device__ __forceinline__ void mbar_arrive(uint32_t bar) {
  asm volatile("mbarrier.arrive.shared::cta.b64 _, [%0];" ::"r"(bar) : "memory");
}
__device__ __forceinline__ void mbar_arrive_remote(uint32_t bar, uint32_t cta) {
  asm volatile("{\n.reg .b32 ra;\nmapa.shared::cluster.u32 ra, %0, %1;\n"
               "mbarrier.arrive.shared::cluster.b64 _, [ra];\n}\n" ::"r"(bar), "r"(cta) : "memory");
}
__device__ __forceinline__ void mbar_wait(uint32_t bar, uint32_t parity) {
  asm volatile("{\n.reg .pred p;\nLAB_WAIT:\n"
               "mbarrier.try_wait.parity.shared::cta.b64 p, [%0], %1, 0x989680;\n"
               "@p bra LAB_DONE;\nbra LAB_WAIT;\nLAB_DONE:\n}\n" ::"r"(bar), "r"(parity) : "memory");
}
__device__ __forceinline__ void mbar_wait_cluster(uint32_t bar, uint32_t parity) {
  asm volatile("{\n.reg .pred p;\nLAB_WAIT:\n"
               "mbarrier.try_wait.parity.acquire.cluster.shared::cta.b64 p, [%0], %1, 0x989680;\n"
               "@p bra LAB_DONE;\nbra LAB_WAIT;\nLAB_DONE:\n}\n" ::"r"(bar), "r"(parity) : "memory");
}
__device__ __forceinline__ void tma_load(uint32_t dst, const CUtensorMap* m, int c0, int c1, uint32_t bar) {
  asm volatile("cp.async.bulk.tensor.2d.shared::cluster.global.mbarrier::complete_tx::bytes [%0], [%1, {%3, %4}], [%2];"
               ::"r"(dst), "l"(m), "r"(bar), "r"(c0), "r"(c1) : "memory");
}
__device__ __forceinline__ void tma_load_mc(uint32_t dst, const CUtensorMap* m, int c0, int c1, uint32_t bar, uint16_t mask) {
  asm volatile("cp.async.bulk.tensor.2d.shared::cluster.global.mbarrier::complete_tx::bytes.multicast::cluster [%0], [%1, {%3, %4}], [%2], %5;"
               ::"r"(dst), "l"(m), "r"(bar), "r"(c0), "r"(c1), "h"(mask) : "memory");
}
__device__ __forceinline__ void cluster_sync_all() {
  asm volatile("barrier.cluster.arrive.release.aligned;\nbarrier.cluster.wait.acquire.aligned;\n" ::: "memory");
}
__device__ __forceinline__ uint32_t cluster_rank() { uint32_t r; asm volatile("mov.u32 %0, %%cluster_ctarank;" : "=r"(r)); return r; }
__device__ __forceinline__ void wg_fence() { asm volatile("wgmma.fence.sync.aligned;" ::: "memory"); }
__device__ __forceinline__ void wg_commit() { asm volatile("wgmma.commit_group.sync.aligned;" ::: "memory"); }
template <int N> __device__ __forceinline__ void wg_wait() { asm volatile("wgmma.wait_group.sync.aligned %0;" ::"n"(N) : "memory"); }
__device__ __forceinline__ void bar_sync(int id, int n) { asm volatile("bar.sync %0, %1;" ::"r"(id), "r"(n) : "memory"); }
__device__ __forceinline__ void bar_arrive(int id, int n) { asm volatile("bar.arrive %0, %1;" ::"r"(id), "r"(n) : "memory"); }
__device__ __forceinline__ void fence_async_smem() { asm volatile("fence.proxy.async.shared::cta;" ::: "memory"); }
__device__ __forceinline__ void fence_async() { asm volatile("fence.proxy.async;" ::: "memory"); }
__device__ __forceinline__ uint64_t mk_desc(uint32_t saddr, uint32_t lbo, uint32_t sbo) {
  return (uint64_t)((saddr & 0x3FFFF) >> 4) | ((uint64_t)(lbo >> 4) << 16) | ((uint64_t)(sbo >> 4) << 32) | (1ull << 62);
}
__device__ __forceinline__ uint32_t pack_bf16(float lo, float hi) {
  uint32_t r; asm("cvt.rn.bf16x2.f32 %0, %1, %2;" : "=r"(r) : "f"(hi), "f"(lo)); return r;
}
__device__ __forceinline__ float bf_lo(uint32_t v) { return __uint_as_float(v << 16); }
__device__ __forceinline__ float bf_hi(uint32_t v) { return __uint_as_float(v & 0xFFFF0000u); }
__device__ __forceinline__ float rbf(float x) { return __bfloat162float(__float2bfloat16_rn(x)); }
__device__ __forceinline__ float ex2(float x) { float r; asm("ex2.approx.ftz.f32 %0, %1;" : "=f"(r) : "f"(x)); return r; }
__device__ __forceinline__ void red_add_v2(float* p, float a, float b) {
  asm volatile("red.global.add.v2.f32 [%0], {%1, %2};" ::"l"(p), "f"(a), "f"(b) : "memory");
}
__device__ __forceinline__ void pdl_wait() { asm volatile("griddepcontrol.wait;" ::: "memory"); }
__device__ __forceinline__ void pdl_launch() { asm volatile("griddepcontrol.launch_dependents;" ::: "memory"); }

__device__ __forceinline__ void wgmma_m64n256k16_ss_tb(float (&d)[128], uint64_t da, uint64_t db, int sc) {
  asm volatile("{\n.reg .pred p;\nsetp.ne.b32 p, %130, 0;\n"
    "wgmma.mma_async.sync.aligned.m64n256k16.f32.bf16.bf16 {%0, %1, %2, %3, %4, %5, %6, %7, %8, %9, %10, %11, %12, %13, %14, %15, %16, %17, %18, %19, %20, %21, %22, %23, %24, %25, %26, %27, %28, %29, %30, %31, %32, %33, %34, %35, %36, %37, %38, %39, %40, %41, %42, %43, %44, %45, %46, %47, %48, %49, %50, %51, %52, %53, %54, %55, %56, %57, %58, %59, %60, %61, %62, %63, %64, %65, %66, %67, %68, %69, %70, %71, %72, %73, %74, %75, %76, %77, %78, %79, %80, %81, %82, %83, %84, %85, %86, %87, %88, %89, %90, %91, %92, %93, %94, %95, %96, %97, %98, %99, %100, %101, %102, %103, %104, %105, %106, %107, %108, %109, %110, %111, %112, %113, %114, %115, %116, %117, %118, %119, %120, %121, %122, %123, %124, %125, %126, %127}, %128, %129, p, 1, 1, 0, 1;\n}\n"
    : "+f"(d[0]), "+f"(d[1]), "+f"(d[2]), "+f"(d[3]), "+f"(d[4]), "+f"(d[5]), "+f"(d[6]), "+f"(d[7]), "+f"(d[8]), "+f"(d[9]), "+f"(d[10]), "+f"(d[11]), "+f"(d[12]), "+f"(d[13]), "+f"(d[14]), "+f"(d[15]), "+f"(d[16]), "+f"(d[17]), "+f"(d[18]), "+f"(d[19]), "+f"(d[20]), "+f"(d[21]), "+f"(d[22]), "+f"(d[23]), "+f"(d[24]), "+f"(d[25]), "+f"(d[26]), "+f"(d[27]), "+f"(d[28]), "+f"(d[29]), "+f"(d[30]), "+f"(d[31]), "+f"(d[32]), "+f"(d[33]), "+f"(d[34]), "+f"(d[35]), "+f"(d[36]), "+f"(d[37]), "+f"(d[38]), "+f"(d[39]), "+f"(d[40]), "+f"(d[41]), "+f"(d[42]), "+f"(d[43]), "+f"(d[44]), "+f"(d[45]), "+f"(d[46]), "+f"(d[47]), "+f"(d[48]), "+f"(d[49]), "+f"(d[50]), "+f"(d[51]), "+f"(d[52]), "+f"(d[53]), "+f"(d[54]), "+f"(d[55]), "+f"(d[56]), "+f"(d[57]), "+f"(d[58]), "+f"(d[59]), "+f"(d[60]), "+f"(d[61]), "+f"(d[62]), "+f"(d[63]), "+f"(d[64]), "+f"(d[65]), "+f"(d[66]), "+f"(d[67]), "+f"(d[68]), "+f"(d[69]), "+f"(d[70]), "+f"(d[71]), "+f"(d[72]), "+f"(d[73]), "+f"(d[74]), "+f"(d[75]), "+f"(d[76]), "+f"(d[77]), "+f"(d[78]), "+f"(d[79]), "+f"(d[80]), "+f"(d[81]), "+f"(d[82]), "+f"(d[83]), "+f"(d[84]), "+f"(d[85]), "+f"(d[86]), "+f"(d[87]), "+f"(d[88]), "+f"(d[89]), "+f"(d[90]), "+f"(d[91]), "+f"(d[92]), "+f"(d[93]), "+f"(d[94]), "+f"(d[95]), "+f"(d[96]), "+f"(d[97]), "+f"(d[98]), "+f"(d[99]), "+f"(d[100]), "+f"(d[101]), "+f"(d[102]), "+f"(d[103]), "+f"(d[104]), "+f"(d[105]), "+f"(d[106]), "+f"(d[107]), "+f"(d[108]), "+f"(d[109]), "+f"(d[110]), "+f"(d[111]), "+f"(d[112]), "+f"(d[113]), "+f"(d[114]), "+f"(d[115]), "+f"(d[116]), "+f"(d[117]), "+f"(d[118]), "+f"(d[119]), "+f"(d[120]), "+f"(d[121]), "+f"(d[122]), "+f"(d[123]), "+f"(d[124]), "+f"(d[125]), "+f"(d[126]), "+f"(d[127])
    : "l"(da), "l"(db), "r"(sc));
}
__device__ __forceinline__ void wgmma_m64n128k16_ss(float (&d)[64], uint64_t da, uint64_t db, int sc) {
  asm volatile("{\n.reg .pred p;\nsetp.ne.b32 p, %66, 0;\n"
    "wgmma.mma_async.sync.aligned.m64n128k16.f32.bf16.bf16 {%0, %1, %2, %3, %4, %5, %6, %7, %8, %9, %10, %11, %12, %13, %14, %15, %16, %17, %18, %19, %20, %21, %22, %23, %24, %25, %26, %27, %28, %29, %30, %31, %32, %33, %34, %35, %36, %37, %38, %39, %40, %41, %42, %43, %44, %45, %46, %47, %48, %49, %50, %51, %52, %53, %54, %55, %56, %57, %58, %59, %60, %61, %62, %63}, %64, %65, p, 1, 1, 0, 0;\n}\n"
    : "+f"(d[0]), "+f"(d[1]), "+f"(d[2]), "+f"(d[3]), "+f"(d[4]), "+f"(d[5]), "+f"(d[6]), "+f"(d[7]), "+f"(d[8]), "+f"(d[9]), "+f"(d[10]), "+f"(d[11]), "+f"(d[12]), "+f"(d[13]), "+f"(d[14]), "+f"(d[15]), "+f"(d[16]), "+f"(d[17]), "+f"(d[18]), "+f"(d[19]), "+f"(d[20]), "+f"(d[21]), "+f"(d[22]), "+f"(d[23]), "+f"(d[24]), "+f"(d[25]), "+f"(d[26]), "+f"(d[27]), "+f"(d[28]), "+f"(d[29]), "+f"(d[30]), "+f"(d[31]), "+f"(d[32]), "+f"(d[33]), "+f"(d[34]), "+f"(d[35]), "+f"(d[36]), "+f"(d[37]), "+f"(d[38]), "+f"(d[39]), "+f"(d[40]), "+f"(d[41]), "+f"(d[42]), "+f"(d[43]), "+f"(d[44]), "+f"(d[45]), "+f"(d[46]), "+f"(d[47]), "+f"(d[48]), "+f"(d[49]), "+f"(d[50]), "+f"(d[51]), "+f"(d[52]), "+f"(d[53]), "+f"(d[54]), "+f"(d[55]), "+f"(d[56]), "+f"(d[57]), "+f"(d[58]), "+f"(d[59]), "+f"(d[60]), "+f"(d[61]), "+f"(d[62]), "+f"(d[63])
    : "l"(da), "l"(db), "r"(sc));
}
__device__ __forceinline__ void wgmma_m64n256k16_rs_tb(float (&d)[128], uint32_t a0, uint32_t a1, uint32_t a2, uint32_t a3, uint64_t db, int sc) {
  asm volatile("{\n.reg .pred p;\nsetp.ne.b32 p, %133, 0;\n"
    "wgmma.mma_async.sync.aligned.m64n256k16.f32.bf16.bf16 {%0, %1, %2, %3, %4, %5, %6, %7, %8, %9, %10, %11, %12, %13, %14, %15, %16, %17, %18, %19, %20, %21, %22, %23, %24, %25, %26, %27, %28, %29, %30, %31, %32, %33, %34, %35, %36, %37, %38, %39, %40, %41, %42, %43, %44, %45, %46, %47, %48, %49, %50, %51, %52, %53, %54, %55, %56, %57, %58, %59, %60, %61, %62, %63, %64, %65, %66, %67, %68, %69, %70, %71, %72, %73, %74, %75, %76, %77, %78, %79, %80, %81, %82, %83, %84, %85, %86, %87, %88, %89, %90, %91, %92, %93, %94, %95, %96, %97, %98, %99, %100, %101, %102, %103, %104, %105, %106, %107, %108, %109, %110, %111, %112, %113, %114, %115, %116, %117, %118, %119, %120, %121, %122, %123, %124, %125, %126, %127}, {%128, %129, %130, %131}, %132, p, 1, 1, 1;\n}\n"
    : "+f"(d[0]), "+f"(d[1]), "+f"(d[2]), "+f"(d[3]), "+f"(d[4]), "+f"(d[5]), "+f"(d[6]), "+f"(d[7]), "+f"(d[8]), "+f"(d[9]), "+f"(d[10]), "+f"(d[11]), "+f"(d[12]), "+f"(d[13]), "+f"(d[14]), "+f"(d[15]), "+f"(d[16]), "+f"(d[17]), "+f"(d[18]), "+f"(d[19]), "+f"(d[20]), "+f"(d[21]), "+f"(d[22]), "+f"(d[23]), "+f"(d[24]), "+f"(d[25]), "+f"(d[26]), "+f"(d[27]), "+f"(d[28]), "+f"(d[29]), "+f"(d[30]), "+f"(d[31]), "+f"(d[32]), "+f"(d[33]), "+f"(d[34]), "+f"(d[35]), "+f"(d[36]), "+f"(d[37]), "+f"(d[38]), "+f"(d[39]), "+f"(d[40]), "+f"(d[41]), "+f"(d[42]), "+f"(d[43]), "+f"(d[44]), "+f"(d[45]), "+f"(d[46]), "+f"(d[47]), "+f"(d[48]), "+f"(d[49]), "+f"(d[50]), "+f"(d[51]), "+f"(d[52]), "+f"(d[53]), "+f"(d[54]), "+f"(d[55]), "+f"(d[56]), "+f"(d[57]), "+f"(d[58]), "+f"(d[59]), "+f"(d[60]), "+f"(d[61]), "+f"(d[62]), "+f"(d[63]), "+f"(d[64]), "+f"(d[65]), "+f"(d[66]), "+f"(d[67]), "+f"(d[68]), "+f"(d[69]), "+f"(d[70]), "+f"(d[71]), "+f"(d[72]), "+f"(d[73]), "+f"(d[74]), "+f"(d[75]), "+f"(d[76]), "+f"(d[77]), "+f"(d[78]), "+f"(d[79]), "+f"(d[80]), "+f"(d[81]), "+f"(d[82]), "+f"(d[83]), "+f"(d[84]), "+f"(d[85]), "+f"(d[86]), "+f"(d[87]), "+f"(d[88]), "+f"(d[89]), "+f"(d[90]), "+f"(d[91]), "+f"(d[92]), "+f"(d[93]), "+f"(d[94]), "+f"(d[95]), "+f"(d[96]), "+f"(d[97]), "+f"(d[98]), "+f"(d[99]), "+f"(d[100]), "+f"(d[101]), "+f"(d[102]), "+f"(d[103]), "+f"(d[104]), "+f"(d[105]), "+f"(d[106]), "+f"(d[107]), "+f"(d[108]), "+f"(d[109]), "+f"(d[110]), "+f"(d[111]), "+f"(d[112]), "+f"(d[113]), "+f"(d[114]), "+f"(d[115]), "+f"(d[116]), "+f"(d[117]), "+f"(d[118]), "+f"(d[119]), "+f"(d[120]), "+f"(d[121]), "+f"(d[122]), "+f"(d[123]), "+f"(d[124]), "+f"(d[125]), "+f"(d[126]), "+f"(d[127])
    : "r"(a0), "r"(a1), "r"(a2), "r"(a3), "l"(db), "r"(sc));
}
__device__ __forceinline__ void wgmma_m64n128k16_ss_tb(float (&d)[64], uint64_t da, uint64_t db, int sc) {
  asm volatile("{\n.reg .pred p;\nsetp.ne.b32 p, %66, 0;\n"
    "wgmma.mma_async.sync.aligned.m64n128k16.f32.bf16.bf16 {%0, %1, %2, %3, %4, %5, %6, %7, %8, %9, %10, %11, %12, %13, %14, %15, %16, %17, %18, %19, %20, %21, %22, %23, %24, %25, %26, %27, %28, %29, %30, %31, %32, %33, %34, %35, %36, %37, %38, %39, %40, %41, %42, %43, %44, %45, %46, %47, %48, %49, %50, %51, %52, %53, %54, %55, %56, %57, %58, %59, %60, %61, %62, %63}, %64, %65, p, 1, 1, 0, 1;\n}\n"
    : "+f"(d[0]), "+f"(d[1]), "+f"(d[2]), "+f"(d[3]), "+f"(d[4]), "+f"(d[5]), "+f"(d[6]), "+f"(d[7]), "+f"(d[8]), "+f"(d[9]), "+f"(d[10]), "+f"(d[11]), "+f"(d[12]), "+f"(d[13]), "+f"(d[14]), "+f"(d[15]), "+f"(d[16]), "+f"(d[17]), "+f"(d[18]), "+f"(d[19]), "+f"(d[20]), "+f"(d[21]), "+f"(d[22]), "+f"(d[23]), "+f"(d[24]), "+f"(d[25]), "+f"(d[26]), "+f"(d[27]), "+f"(d[28]), "+f"(d[29]), "+f"(d[30]), "+f"(d[31]), "+f"(d[32]), "+f"(d[33]), "+f"(d[34]), "+f"(d[35]), "+f"(d[36]), "+f"(d[37]), "+f"(d[38]), "+f"(d[39]), "+f"(d[40]), "+f"(d[41]), "+f"(d[42]), "+f"(d[43]), "+f"(d[44]), "+f"(d[45]), "+f"(d[46]), "+f"(d[47]), "+f"(d[48]), "+f"(d[49]), "+f"(d[50]), "+f"(d[51]), "+f"(d[52]), "+f"(d[53]), "+f"(d[54]), "+f"(d[55]), "+f"(d[56]), "+f"(d[57]), "+f"(d[58]), "+f"(d[59]), "+f"(d[60]), "+f"(d[61]), "+f"(d[62]), "+f"(d[63])
    : "l"(da), "l"(db), "r"(sc));
}
__device__ __forceinline__ void wgmma_m64n128k16_rs_tb(float (&d)[64], uint32_t a0, uint32_t a1, uint32_t a2, uint32_t a3, uint64_t db, int sc) {
  asm volatile("{\n.reg .pred p;\nsetp.ne.b32 p, %69, 0;\n"
    "wgmma.mma_async.sync.aligned.m64n128k16.f32.bf16.bf16 {%0, %1, %2, %3, %4, %5, %6, %7, %8, %9, %10, %11, %12, %13, %14, %15, %16, %17, %18, %19, %20, %21, %22, %23, %24, %25, %26, %27, %28, %29, %30, %31, %32, %33, %34, %35, %36, %37, %38, %39, %40, %41, %42, %43, %44, %45, %46, %47, %48, %49, %50, %51, %52, %53, %54, %55, %56, %57, %58, %59, %60, %61, %62, %63}, {%64, %65, %66, %67}, %68, p, 1, 1, 1;\n}\n"
    : "+f"(d[0]), "+f"(d[1]), "+f"(d[2]), "+f"(d[3]), "+f"(d[4]), "+f"(d[5]), "+f"(d[6]), "+f"(d[7]), "+f"(d[8]), "+f"(d[9]), "+f"(d[10]), "+f"(d[11]), "+f"(d[12]), "+f"(d[13]), "+f"(d[14]), "+f"(d[15]), "+f"(d[16]), "+f"(d[17]), "+f"(d[18]), "+f"(d[19]), "+f"(d[20]), "+f"(d[21]), "+f"(d[22]), "+f"(d[23]), "+f"(d[24]), "+f"(d[25]), "+f"(d[26]), "+f"(d[27]), "+f"(d[28]), "+f"(d[29]), "+f"(d[30]), "+f"(d[31]), "+f"(d[32]), "+f"(d[33]), "+f"(d[34]), "+f"(d[35]), "+f"(d[36]), "+f"(d[37]), "+f"(d[38]), "+f"(d[39]), "+f"(d[40]), "+f"(d[41]), "+f"(d[42]), "+f"(d[43]), "+f"(d[44]), "+f"(d[45]), "+f"(d[46]), "+f"(d[47]), "+f"(d[48]), "+f"(d[49]), "+f"(d[50]), "+f"(d[51]), "+f"(d[52]), "+f"(d[53]), "+f"(d[54]), "+f"(d[55]), "+f"(d[56]), "+f"(d[57]), "+f"(d[58]), "+f"(d[59]), "+f"(d[60]), "+f"(d[61]), "+f"(d[62]), "+f"(d[63])
    : "r"(a0), "r"(a1), "r"(a2), "r"(a3), "l"(db), "r"(sc));
}
__device__ __forceinline__ void wgmma_m64n64k16_ss_tb(float (&d)[32], uint64_t da, uint64_t db, int sc) {
  asm volatile("{\n.reg .pred p;\nsetp.ne.b32 p, %34, 0;\n"
    "wgmma.mma_async.sync.aligned.m64n64k16.f32.bf16.bf16 {%0, %1, %2, %3, %4, %5, %6, %7, %8, %9, %10, %11, %12, %13, %14, %15, %16, %17, %18, %19, %20, %21, %22, %23, %24, %25, %26, %27, %28, %29, %30, %31}, %32, %33, p, 1, 1, 0, 1;\n}\n"
    : "+f"(d[0]), "+f"(d[1]), "+f"(d[2]), "+f"(d[3]), "+f"(d[4]), "+f"(d[5]), "+f"(d[6]), "+f"(d[7]), "+f"(d[8]), "+f"(d[9]), "+f"(d[10]), "+f"(d[11]), "+f"(d[12]), "+f"(d[13]), "+f"(d[14]), "+f"(d[15]), "+f"(d[16]), "+f"(d[17]), "+f"(d[18]), "+f"(d[19]), "+f"(d[20]), "+f"(d[21]), "+f"(d[22]), "+f"(d[23]), "+f"(d[24]), "+f"(d[25]), "+f"(d[26]), "+f"(d[27]), "+f"(d[28]), "+f"(d[29]), "+f"(d[30]), "+f"(d[31])
    : "l"(da), "l"(db), "r"(sc));
}
__device__ __forceinline__ void wgmma_m64n64k16_rs_tb(float (&d)[32], uint32_t a0, uint32_t a1, uint32_t a2, uint32_t a3, uint64_t db, int sc) {
  asm volatile("{\n.reg .pred p;\nsetp.ne.b32 p, %37, 0;\n"
    "wgmma.mma_async.sync.aligned.m64n64k16.f32.bf16.bf16 {%0, %1, %2, %3, %4, %5, %6, %7, %8, %9, %10, %11, %12, %13, %14, %15, %16, %17, %18, %19, %20, %21, %22, %23, %24, %25, %26, %27, %28, %29, %30, %31}, {%32, %33, %34, %35}, %36, p, 1, 1, 1;\n}\n"
    : "+f"(d[0]), "+f"(d[1]), "+f"(d[2]), "+f"(d[3]), "+f"(d[4]), "+f"(d[5]), "+f"(d[6]), "+f"(d[7]), "+f"(d[8]), "+f"(d[9]), "+f"(d[10]), "+f"(d[11]), "+f"(d[12]), "+f"(d[13]), "+f"(d[14]), "+f"(d[15]), "+f"(d[16]), "+f"(d[17]), "+f"(d[18]), "+f"(d[19]), "+f"(d[20]), "+f"(d[21]), "+f"(d[22]), "+f"(d[23]), "+f"(d[24]), "+f"(d[25]), "+f"(d[26]), "+f"(d[27]), "+f"(d[28]), "+f"(d[29]), "+f"(d[30]), "+f"(d[31])
    : "r"(a0), "r"(a1), "r"(a2), "r"(a3), "l"(db), "r"(sc));
}

#define TM(id)
#define GT_MIN(i)
#define GT_MAX(i)

constexpr int NS = 5;
constexpr uint32_t STG = 32768;
constexpr uint32_t SM_Q = 0;
constexpr uint32_t SM_RING = 65536;
constexpr uint32_t SM_BAR = SM_RING + NS * STG;
constexpr uint32_t SM_TOTAL = SM_BAR + 256 + 1024;

struct Ring {
  uint32_t base, full0, empty0, st, ph, nst;
  __device__ __forceinline__ void init(uint32_t sb) { base = sb + SM_RING; full0 = sb + SM_BAR; empty0 = sb + SM_BAR + 64; st = 0; ph = 0; nst = NS; }
  __device__ __forceinline__ uint32_t phase() const { return (ph >> st) & 1; }
  __device__ __forceinline__ uint32_t buf() const { return base + st * STG; }
  __device__ __forceinline__ uint32_t full() const { return full0 + st * 8; }
  __device__ __forceinline__ uint32_t empty() const { return empty0 + st * 8; }
  __device__ __forceinline__ void next() { ph ^= 1u << st; st = (st + 1 >= nst) ? 0 : st + 1; }
  __device__ __forceinline__ void shrink() { nst = NS - 1; if (st >= nst) st = 0; }
  __device__ __forceinline__ uint32_t acquire(uint32_t bytes) {
    mbar_wait(empty(), phase() ^ 1); mbar_expect_tx(full(), bytes); return buf();
  }
  __device__ __forceinline__ uint32_t wait() { mbar_wait(full(), phase()); return buf(); }
};
__device__ __forceinline__ void ring_release(uint32_t empty_bar, int lane) {
  __syncwarp();
  if (lane < 2) mbar_arrive_remote(empty_bar, (uint32_t)lane);
}

__device__ __forceinline__ void gemm_k448_n256(Ring& r, float (&acc)[128], int wg, int lane) {
  uint32_t hb = 0, hrel = 0, prel = 0, phrel = 0;
#pragma unroll
  for (int c = 0; c < 7; ++c) {
    if ((c & 1) == 0) { hb = r.wait(); hrel = r.empty(); r.next(); }
    uint32_t wb = r.wait(); uint32_t wrel = r.empty(); r.next();
    uint64_t da = mk_desc(hb + (c & 1) * 16384 + wg * 8192, 16, 1024);
    uint64_t db = mk_desc(wb, 8192, 1024);
    wg_fence();
#pragma unroll
    for (int k = 0; k < 4; ++k) wgmma_m64n256k16_ss_tb(acc, da + k * 2, db + k * 128, (c | k) != 0);
    wg_commit();
    if (c > 0) {
      wg_wait<1>();
      ring_release(prel, lane);
      if ((c & 1) == 0) ring_release(phrel, lane);
    }
    prel = wrel; phrel = hrel;
  }
  wg_wait<0>();
  ring_release(prel, lane); ring_release(phrel, lane);
}

template <bool RELU>
__device__ __forceinline__ void store_tile_bf16(uint32_t base, const float (&acc)[128], int rloc, int t4) {
  uint32_t row0 = base + rloc * 128, row1 = row0 + 8 * 128;
  uint32_t sw = (uint32_t)(rloc & 7);
#pragma unroll
  for (int j = 0; j < 32; ++j) {
    uint32_t off = (uint32_t)(j >> 3) * 16384 + ((((uint32_t)j & 7) ^ sw) << 4) + t4 * 4;
    float a = acc[4 * j], b = acc[4 * j + 1], c = acc[4 * j + 2], d = acc[4 * j + 3];
    if (RELU) { a = fmaxf(a, 0.f); b = fmaxf(b, 0.f); c = fmaxf(c, 0.f); d = fmaxf(d, 0.f); }
    asm volatile("st.shared.b32 [%0], %1;" ::"r"(row0 + off), "r"(pack_bf16(a, b)) : "memory");
    asm volatile("st.shared.b32 [%0], %1;" ::"r"(row1 + off), "r"(pack_bf16(c, d)) : "memory");
  }
}

template <int NJ>
__device__ __forceinline__ void red_rows(uint32_t stg, float* dstw, const float (&a)[64], int sel, int lane) {
  const uint32_t g = lane >> 2, t4 = lane & 3;
  const uint32_t wbase = stg + g * 512 + (t4 & 1) * 8, sw = (g & 3) << 1;
#pragma unroll
  for (int j = 0; j < NJ; ++j)
    asm volatile("st.shared.v2.f32 [%0], {%1, %2};" ::"r"(wbase + (((2 * j + (t4 >> 1)) ^ sw) << 4)), "f"(a[4 * j + sel]), "f"(a[4 * j + sel + 1]) : "memory");
  __syncwarp();
  constexpr int LPR = NJ * 2;
  constexpr int RPI = 32 / LPR;
#pragma unroll
  for (int i = 0; i < 8 / RPI; ++i) {
    const uint32_t row = i * RPI + lane / LPR, ch = lane % LPR;
    float x, y, z, w;
    asm volatile("ld.shared.v4.f32 {%0, %1, %2, %3}, [%4];" : "=f"(x), "=f"(y), "=f"(z), "=f"(w)
                 : "r"(stg + row * 512 + ((ch ^ ((row & 3) << 1)) << 4)) : "memory");
    asm volatile("red.global.add.v4.f32 [%0], {%1, %2, %3, %4};" ::"l"(dstw + row * DM + ch * 4), "f"(x), "f"(y), "f"(z), "f"(w) : "memory");
  }
  __syncwarp();
}

template <int NSM, int NRG>
__device__ __forceinline__ void out_proj(Ring& r, const uint32_t (&ob)[64], uint32_t abase,
                                         float* dstw, uint32_t stg, int lane) {
  constexpr int NST = (NSM + NRG) / 2;
  uint32_t prel = 0;
  float accA[64], accB[64];
  float(&cur32)[32] = *reinterpret_cast<float(*)[32]>(&accB[0]);
#pragma unroll
  for (int pass = 0; pass < 4; ++pass) {
    float(&cur)[64] = (pass & 1) ? accB : accA;
    float(&prv)[64] = (pass & 1) ? accA : accB;
#pragma unroll
    for (int st = 0; st < NST; ++st) {
      uint32_t wb = r.wait(); uint32_t rel = r.empty(); r.next();
      wg_fence();
#pragma unroll
      for (int cc = 0; cc < 2; ++cc) {
        const int c = 2 * st + cc;
#pragma unroll
        for (int k = 0; k < 4; ++k) {
          const int sc = (c | k) != 0;
          if (pass < 3) {
            uint64_t db = mk_desc(wb + cc * 16384 + k * 2048, 8192, 1024);
            if (c < NSM) wgmma_m64n128k16_ss_tb(cur, mk_desc(abase + c * 16384 + k * 32, 16, 1024), db, sc);
            else { const int o = (c - NSM) * 16 + 4 * k; wgmma_m64n128k16_rs_tb(cur, ob[o], ob[o + 1], ob[o + 2], ob[o + 3], db, sc); }
          } else {
            uint64_t db = mk_desc(wb + cc * 8192 + k * 2048, 8192, 1024);
            if (c < NSM) wgmma_m64n64k16_ss_tb(cur32, mk_desc(abase + c * 16384 + k * 32, 16, 1024), db, sc);
            else { const int o = (c - NSM) * 16 + 4 * k; wgmma_m64n64k16_rs_tb(cur32, ob[o], ob[o + 1], ob[o + 2], ob[o + 3], db, sc); }
          }
        }
      }
      wg_commit();
      if (pass | st) { wg_wait<1>(); ring_release(prel, lane); }
      prel = rel;
      if (pass > 0) {
        if (st == 0) red_rows<16>(stg, dstw + (pass - 1) * 128, prv, 0, lane);
        if (st == NST / 2) red_rows<16>(stg, dstw + 8 * DM + (pass - 1) * 128, prv, 2, lane);
      }
    }
  }
  wg_wait<0>(); ring_release(prel, lane);
  red_rows<8>(stg, dstw + 384, accB, 0, lane);
  red_rows<8>(stg, dstw + 8 * DM + 384, accB, 2, lane);
}
__device__ __forceinline__ void out_proj_loads(Ring& r, const CUtensorMap* tm, int krow0, int nch, uint32_t rank) {
  r.shrink();
  for (int pass = 0; pass < 4; ++pass)
    for (int st = 0; st < nch / 2; ++st) {
      if (pass < 3) {
        uint32_t b = r.acquire(32768);
        for (int x = 0; x < 2; ++x)
          tma_load_mc(b + rank * 16384 + x * 8192, tm, pass * 128 + x * 64, krow0 + (2 * st + rank) * 64, r.full(), 3);
      } else {
        uint32_t b = r.acquire(16384);
        tma_load_mc(b + rank * 8192, tm, 384, krow0 + (2 * st + rank) * 64, r.full(), 3);
      }
      r.next();
    }
}

__global__ void __cluster_dims__(2, 1, 1) __launch_bounds__(384, 1)
attn_kernel(const __grid_constant__ CUtensorMap tm_h, const __grid_constant__ CUtensorMap tm_wq,
            const __grid_constant__ CUtensorMap tm_k, const __grid_constant__ CUtensorMap tm_v,
            const __grid_constant__ CUtensorMap tm_wo, const __grid_constant__ CUtensorMap tm_oA) {
  extern __shared__ uint8_t smem_raw[];
  const uint32_t sb = (smem_u32(smem_raw) + 1023) & ~1023u;
  const int tid = threadIdx.x, wg = tid >> 7, lane = tid & 31;
  const int qt = blockIdx.x, kvh = blockIdx.y;
  const uint32_t rank = cluster_rank();
  Ring r; r.init(sb);
  const uint32_t bar_oA = sb + SM_BAR + 128, bar_oAf = sb + SM_BAR + 136;
  if (tid == 0) {
    for (int i = 0; i < NS; ++i) { mbar_init(r.full0 + 8 * i, 1); mbar_init(r.empty0 + 8 * i, 16); }
    mbar_init(bar_oA, 256); mbar_init(bar_oAf, 1);
    asm volatile("fence.mbarrier_init.release.cluster;" ::: "memory");
  }
  cluster_sync_all();
  pdl_wait();
  GT_MIN(4);

  if (wg == 2) {
    asm volatile("setmaxnreg.dec.sync.aligned.u32 24;");
    if (tid == 256) {
      const int krow0 = kvh * SKV + (SKV - WIN);
      for (int hh = 0; hh < 2; ++hh) {
        const int head = kvh * 2 + hh;
        for (int p = 0; p < 4; ++p) {
          int nc = (p < 3) ? 2 : 1;
          uint32_t b = r.acquire(nc * 16384);
          for (int c = 0; c < nc; ++c) tma_load(b + c * 16384, &tm_h, (2 * p + c) * 64, qt * 128, r.full());
          r.next();
          for (int c = 0; c < nc; ++c) {
            b = r.acquire(32768);
            for (int x = 0; x < 2; ++x) {
              int bx = rank * 2 + x;
              tma_load_mc(b + bx * 8192, &tm_wq, head * 256 + bx * 64, (2 * p + c) * 64, r.full(), 3);
            }
            r.next();
          }
        }
        for (int t = 0; t < 4; ++t) {
          for (int hf = 0; hf < 2; ++hf) {
            uint32_t b = r.acquire(32768);
            tma_load_mc(b + rank * 16384, &tm_k, (2 * hf + rank) * 64, krow0 + t * 128, r.full(), 3);
            r.next();
          }
          for (int hf = 0; hf < 2; ++hf) {
            uint32_t b = r.acquire(32768);
            for (int x = 0; x < 2; ++x) {
              int bx = rank * 2 + x;
              tma_load_mc(b + bx * 8192, &tm_v, bx * 64, krow0 + t * 128 + hf * 64, r.full(), 3);
            }
            r.next();
          }
        }
      }
      mbar_wait(bar_oA, 0);
      mbar_expect_tx(bar_oAf, 65536);
      for (int c = 0; c < 4; ++c) tma_load(sb + SM_Q + c * 16384, &tm_oA, c * 64, kvh * SEQ + qt * 128, bar_oAf);
      out_proj_loads(r, &tm_wo, kvh * 512, 8, rank);
    }
  } else {
    asm volatile("setmaxnreg.inc.sync.aligned.u32 240;");
    const int warp = (tid >> 5) & 3, g = lane >> 2, t4 = lane & 3;
    const int rloc = wg * 64 + warp * 16 + g;
    uint32_t ob[64];
    float acc[128];
    const float CS = 1.4426950408889634f * 0.0625f;
    TM(0);
#pragma unroll 1
    for (int hh = 0; hh < 2; ++hh) {
      gemm_k448_n256(r, acc, wg, lane);
      TM(1);
      store_tile_bf16<false>(sb + SM_Q, acc, rloc, t4);
      fence_async_smem();
      if (hh == 1) fence_async();
      bar_sync(1 + wg, 128);
      float m0 = -INFINITY, m1 = -INFINITY, l0 = 0.f, l1 = 0.f;
      const uint32_t qa0 = sb + SM_Q + wg * 8192;
      if (wg == 1) bar_arrive(3, 256);
      TM(2);
      bar_sync(3 + wg, 256);
#pragma unroll 1
      for (int t = 0; t < 4; ++t) {
        float s[64];
        TM(3);
        {
          uint32_t qa = qa0; asm volatile("" : "+r"(qa));
          uint32_t ka = r.wait(); uint32_t rel0 = r.empty(); r.next();
          wg_fence();
#pragma unroll
          for (int k = 0; k < 8; ++k)
            wgmma_m64n128k16_ss(s, mk_desc(qa + (k >> 2) * 16384 + (k & 3) * 32, 16, 1024),
                                mk_desc(ka + (k >> 2) * 16384 + (k & 3) * 32, 16, 1024), k != 0);
          wg_commit();
          uint32_t kb = r.wait(); uint32_t rel1 = r.empty(); r.next();
          wg_fence();
#pragma unroll
          for (int k = 0; k < 8; ++k)
            wgmma_m64n128k16_ss(s, mk_desc(qa + (2 + (k >> 2)) * 16384 + (k & 3) * 32, 16, 1024),
                                mk_desc(kb + (k >> 2) * 16384 + (k & 3) * 32, 16, 1024), 1);
          wg_commit();
          bar_arrive(4 - wg, 256);
          wg_wait<1>(); ring_release(rel0, lane);
          wg_wait<0>(); ring_release(rel1, lane);
        }
        TM(4);
        float mx0 = m0, mx1 = m1;
#pragma unroll
        for (int j = 0; j < 16; ++j) {
          uint32_t a = pack_bf16(s[4 * j], s[4 * j + 1]), b = pack_bf16(s[4 * j + 2], s[4 * j + 3]);
          s[4 * j] = bf_lo(a); s[4 * j + 1] = bf_hi(a); s[4 * j + 2] = bf_lo(b); s[4 * j + 3] = bf_hi(b);
          mx0 = fmaxf(mx0, fmaxf(s[4 * j], s[4 * j + 1])); mx1 = fmaxf(mx1, fmaxf(s[4 * j + 2], s[4 * j + 3]));
        }
        mx0 = fmaxf(mx0, __shfl_xor_sync(0xffffffffu, mx0, 1)); mx0 = fmaxf(mx0, __shfl_xor_sync(0xffffffffu, mx0, 2));
        mx1 = fmaxf(mx1, __shfl_xor_sync(0xffffffffu, mx1, 1)); mx1 = fmaxf(mx1, __shfl_xor_sync(0xffffffffu, mx1, 2));
        const float c0 = ex2((m0 - mx0) * CS), c1 = ex2((m1 - mx1) * CS);
        m0 = mx0; m1 = mx1;
        const float nb0 = -mx0 * CS, nb1 = -mx1 * CS;
        float ps0 = 0.f, ps1 = 0.f;
        uint32_t pa[32];
#pragma unroll
        for (int j = 0; j < 16; ++j) {
          float e0 = ex2(fmaf(s[4 * j], CS, nb0)), e1 = ex2(fmaf(s[4 * j + 1], CS, nb0));
          float e2 = ex2(fmaf(s[4 * j + 2], CS, nb1)), e3 = ex2(fmaf(s[4 * j + 3], CS, nb1));
          ps0 += e0 + e1; ps1 += e2 + e3;
          pa[2 * j] = pack_bf16(e0, e1); pa[2 * j + 1] = pack_bf16(e2, e3);
        }
        l0 = l0 * c0 + ps0; l1 = l1 * c1 + ps1;
        if (t > 0) {
#pragma unroll
          for (int j = 0; j < 32; ++j) { acc[4 * j] *= c0; acc[4 * j + 1] *= c0; acc[4 * j + 2] *= c1; acc[4 * j + 3] *= c1; }
        }
#pragma unroll
        for (int j = 0; j < 32; ++j) asm volatile("" : "+r"(pa[j]));
#pragma unroll
        for (int j = 0; j < 128; ++j) asm volatile("" : "+f"(acc[j]));
        asm volatile("" : "+f"(l0), "+f"(l1));
        TM(5);
        bar_sync(3 + wg, 256);
        TM(6);
        {
          uint32_t va = r.wait(); uint32_t rel0 = r.empty(); r.next();
          wg_fence();
#pragma unroll
          for (int k = 0; k < 4; ++k)
            wgmma_m64n256k16_rs_tb(acc, pa[4 * k], pa[4 * k + 1], pa[4 * k + 2], pa[4 * k + 3],
                                   mk_desc(va + k * 2048, 8192, 1024), (t | k) != 0);
          wg_commit();
          uint32_t vb = r.wait(); uint32_t rel1 = r.empty(); r.next();
          wg_fence();
#pragma unroll
          for (int k = 0; k < 4; ++k)
            wgmma_m64n256k16_rs_tb(acc, pa[16 + 4 * k], pa[16 + 4 * k + 1], pa[16 + 4 * k + 2], pa[16 + 4 * k + 3],
                                   mk_desc(vb + k * 2048, 8192, 1024), 1);
          wg_commit();
          if (t == 3 && wg == 0) bar_arrive(4, 256);
          wg_wait<1>(); ring_release(rel0, lane);
          wg_wait<0>(); ring_release(rel1, lane);
        }
      }
      TM(7);
      l0 += __shfl_xor_sync(0xffffffffu, l0, 1); l0 += __shfl_xor_sync(0xffffffffu, l0, 2);
      l1 += __shfl_xor_sync(0xffffffffu, l1, 1); l1 += __shfl_xor_sync(0xffffffffu, l1, 2);
      const float i0 = 1.f / l0, i1 = 1.f / l1;
#pragma unroll
      for (int j = 0; j < 32; ++j) {
        ob[2 * j] = pack_bf16(acc[4 * j] * i0, acc[4 * j + 1] * i0);
        ob[2 * j + 1] = pack_bf16(acc[4 * j + 2] * i1, acc[4 * j + 3] * i1);
      }
      if (hh == 0) {
        uint32_t* o0 = reinterpret_cast<uint32_t*>(g_oA + ((size_t)kvh * SEQ + qt * 128 + rloc) * DH) + t4;
#pragma unroll
        for (int j = 0; j < 32; ++j) { o0[4 * j] = ob[2 * j]; o0[4 * j + 8 * DH / 2] = ob[2 * j + 1]; }
      }
    }
    mbar_arrive(bar_oA);
    mbar_wait(bar_oAf, 0);
    TM(8);
    r.shrink();
    out_proj<4, 4>(r, ob, sb + SM_Q + wg * 8192, g_acc1 + (size_t)(qt * 128 + wg * 64 + warp * 16) * DM,
                   sb + SM_RING + (NS - 1) * STG + (wg * 4 + warp) * 4096, lane);
    TM(9);
  }
  cluster_sync_all();
  GT_MAX(5);
}

__global__ void __cluster_dims__(2, 1, 1) __launch_bounds__(384, 1)
ffn_kernel(const __grid_constant__ CUtensorMap tm_h2, const __grid_constant__ CUtensorMap tm_w1,
           const __grid_constant__ CUtensorMap tm_w2) {
  extern __shared__ uint8_t smem_raw[];
  const uint32_t sb = (smem_u32(smem_raw) + 1023) & ~1023u;
  const int tid = threadIdx.x, wg = tid >> 7, lane = tid & 31;
  const int rt = blockIdx.x, sl = blockIdx.y;
  const uint32_t rank = cluster_rank();
  Ring r; r.init(sb);
  if (tid == 0) {
    for (int i = 0; i < NS; ++i) { mbar_init(r.full0 + 8 * i, 1); mbar_init(r.empty0 + 8 * i, 16); }
    asm volatile("fence.mbarrier_init.release.cluster;" ::: "memory");
  }
  cluster_sync_all();
  pdl_wait();
  GT_MIN(8);
  if (wg == 2) {
    asm volatile("setmaxnreg.dec.sync.aligned.u32 24;");
    if (tid == 256) {
      for (int p = 0; p < 4; ++p) {
        int nc = (p < 3) ? 2 : 1;
        uint32_t b = r.acquire(nc * 16384);
        for (int c = 0; c < nc; ++c) tma_load(b + c * 16384, &tm_h2, (2 * p + c) * 64, rt * 128, r.full());
        r.next();
        for (int c = 0; c < nc; ++c) {
          b = r.acquire(32768);
          for (int x = 0; x < 2; ++x) {
            int bx = rank * 2 + x;
            tma_load_mc(b + bx * 8192, &tm_w1, sl * 256 + bx * 64, (2 * p + c) * 64, r.full(), 3);
          }
          r.next();
        }
      }
      out_proj_loads(r, &tm_w2, sl * 256, 4, rank);
    }
  } else {
    asm volatile("setmaxnreg.inc.sync.aligned.u32 240;");
    const int warp = (tid >> 5) & 3, g = lane >> 2, t4 = lane & 3;
    const int rloc = wg * 64 + warp * 16 + g;
    uint32_t ob[64];
    {
      float acc[128];
      TM(20);
      gemm_k448_n256(r, acc, wg, lane);
      TM(21);
      store_tile_bf16<true>(sb + SM_Q, acc, rloc, t4);
    }
    fence_async_smem();
    bar_sync(5, 256);
    TM(22);
    r.shrink();
    out_proj<4, 0>(r, ob, sb + SM_Q + wg * 8192, g_acc2 + (size_t)(rt * 128 + wg * 64 + warp * 16) * DM,
                   sb + SM_RING + (NS - 1) * STG + (wg * 4 + warp) * 4096, lane);
    TM(23);
  }
  cluster_sync_all();
  GT_MAX(9);
}

__global__ void __launch_bounds__(512) mod_kernel(const __nv_bfloat16* __restrict__ c, const __nv_bfloat16* __restrict__ wm) {
  __shared__ float red[32][33];
  const int tid = threadIdx.x;
  GT_MIN(0);
  if (blockIdx.x < 84) {
    const int cl = tid & 15, kg = tid >> 4;
    const int col = blockIdx.x * 32 + cl * 2;
    uint32_t v[14];
#pragma unroll
    for (int i = 0; i < 14; ++i) v[i] = *reinterpret_cast<const uint32_t*>(wm + (size_t)(kg * 14 + i) * (6 * DM) + col);
    float a0 = 0.f, a1 = 0.f;
#pragma unroll
    for (int i = 0; i < 14; ++i) {
      float cv = __bfloat162float(c[kg * 14 + i]);
      float sv = rbf(cv / (1.f + __expf(-cv)));
      a0 = fmaf(sv, bf_lo(v[i]), a0); a1 = fmaf(sv, bf_hi(v[i]), a1);
    }
    red[kg][cl * 2] = a0; red[kg][cl * 2 + 1] = a1;
    __syncthreads();
    if (tid < 32) {
      float s = 0.f;
#pragma unroll
      for (int i = 0; i < 32; ++i) s += red[i][tid];
      g_mod[blockIdx.x * 32 + tid] = rbf(s);
    }
  } else {
    float4 z = make_float4(0.f, 0.f, 0.f, 0.f);
    const int n4 = SEQ * DM / 4;
    for (int i = (blockIdx.x - 84) * 512 + tid; i < n4; i += (gridDim.x - 84) * 512) {
      reinterpret_cast<float4*>(g_acc1)[i] = z; reinterpret_cast<float4*>(g_acc2)[i] = z;
    }
  }
  if (blockIdx.x < 84) GT_MAX(1); else GT_MAX(13);
  pdl_launch();
}

__device__ __forceinline__ void ln_row(const float (&x)[14], const float* __restrict__ shift, const float* __restrict__ scale,
                                       __nv_bfloat16* __restrict__ out, int lane) {
  float2 sc[7], sh[7];
#pragma unroll
  for (int i = 0; i < 7; ++i) {
    sc[i] = *reinterpret_cast<const float2*>(scale + i * 64 + lane * 2);
    sh[i] = *reinterpret_cast<const float2*>(shift + i * 64 + lane * 2);
  }
  float s = 0.f;
#pragma unroll
  for (int i = 0; i < 14; ++i) s += x[i];
#pragma unroll
  for (int o = 16; o; o >>= 1) s += __shfl_xor_sync(0xffffffffu, s, o);
  const float mean = s * (1.f / DM);
  float q = 0.f;
#pragma unroll
  for (int i = 0; i < 14; ++i) { float d = x[i] - mean; q = fmaf(d, d, q); }
#pragma unroll
  for (int o = 16; o; o >>= 1) q += __shfl_xor_sync(0xffffffffu, q, o);
  const float mb = rbf(mean), vb = rbf(q * (1.f / DM));
  const float den = rbf(sqrtf(rbf(vb + 1e-5f)));
#pragma unroll
  for (int i = 0; i < 7; ++i) {
    int col = i * 64 + lane * 2;
    float y0 = rbf(rbf(x[2 * i] - mb) / den), y1 = rbf(rbf(x[2 * i + 1] - mb) / den);
    y0 = rbf(y0 * rbf(1.f + sc[i].x)); y1 = rbf(y1 * rbf(1.f + sc[i].y));
    *reinterpret_cast<uint32_t*>(out + col) = pack_bf16(y0 + sh[i].x, y1 + sh[i].y);
  }
}

__global__ void __launch_bounds__(256) ln1_kernel(const __nv_bfloat16* __restrict__ x) {
  const int lane = threadIdx.x & 31, row = blockIdx.x * 8 + (threadIdx.x >> 5);
  float v[14];
#pragma unroll
  for (int i = 0; i < 7; ++i) {
    uint32_t u = *reinterpret_cast<const uint32_t*>(x + (size_t)row * DM + i * 64 + lane * 2);
    v[2 * i] = bf_lo(u); v[2 * i + 1] = bf_hi(u);
  }
  pdl_wait();
  GT_MIN(2);
  ln_row(v, g_mod + 0 * DM, g_mod + 1 * DM, g_h + (size_t)row * DM, lane);
  GT_MAX(3);
  pdl_launch();
}

__global__ void __launch_bounds__(256) ln2_kernel(const __nv_bfloat16* __restrict__ x) {
  const int lane = threadIdx.x & 31, row = blockIdx.x * 8 + (threadIdx.x >> 5);
  float v[14];
  uint32_t xu[7];
#pragma unroll
  for (int i = 0; i < 7; ++i) xu[i] = *reinterpret_cast<const uint32_t*>(x + (size_t)row * DM + i * 64 + lane * 2);
  pdl_wait();
  GT_MIN(6);
  float2 av[7], gv[7];
#pragma unroll
  for (int i = 0; i < 7; ++i) {
    av[i] = *reinterpret_cast<const float2*>(g_acc1 + (size_t)row * DM + i * 64 + lane * 2);
    gv[i] = *reinterpret_cast<const float2*>(g_mod + 2 * DM + i * 64 + lane * 2);
  }
#pragma unroll
  for (int i = 0; i < 7; ++i) {
    int col = i * 64 + lane * 2;
    uint32_t u = xu[i];
    float t0 = rbf(gv[i].x * rbf(av[i].x)), t1 = rbf(gv[i].y * rbf(av[i].y));
    v[2 * i] = rbf(bf_lo(u) + t0); v[2 * i + 1] = rbf(bf_hi(u) + t1);
    *reinterpret_cast<uint32_t*>(g_x1 + (size_t)row * DM + col) = pack_bf16(v[2 * i], v[2 * i + 1]);
  }
  ln_row(v, g_mod + 3 * DM, g_mod + 4 * DM, g_h2 + (size_t)row * DM, lane);
  GT_MAX(7);
  pdl_launch();
}

__global__ void __launch_bounds__(256) final_kernel(__nv_bfloat16* __restrict__ out) {
  pdl_wait();
  GT_MIN(10);
  const int i = blockIdx.x * 256 + threadIdx.x;
  const int col = (i * 2) % DM;
  uint32_t u = reinterpret_cast<const uint32_t*>(g_x1)[i];
  float2 a = reinterpret_cast<const float2*>(g_acc2)[i];
  float t0 = rbf(g_mod[5 * DM + col] * rbf(a.x)), t1 = rbf(g_mod[5 * DM + col + 1] * rbf(a.y));
  reinterpret_cast<uint32_t*>(out)[i] = pack_bf16(bf_lo(u) + t0, bf_hi(u) + t1);
  GT_MAX(11);
}

typedef CUresult (*EncodeFn)(CUtensorMap*, CUtensorMapDataType, cuuint32_t, void*, const cuuint64_t*, const cuuint64_t*,
                             const cuuint32_t*, const cuuint32_t*, CUtensorMapInterleave, CUtensorMapSwizzle,
                             CUtensorMapL2promotion, CUtensorMapFloatOOBfill);

static CUtensorMap make_map(EncodeFn enc, const void* ptr, uint64_t cols, uint64_t rows, uint32_t bx, uint32_t by) {
  CUtensorMap m;
  cuuint64_t dims[2] = {cols, rows};
  cuuint64_t strides[1] = {cols * 2};
  cuuint32_t box[2] = {bx, by};
  cuuint32_t es[2] = {1, 1};
  enc(&m, CU_TENSOR_MAP_DATA_TYPE_BFLOAT16, 2, const_cast<void*>(ptr), dims, strides, box, es, CU_TENSOR_MAP_INTERLEAVE_NONE,
      CU_TENSOR_MAP_SWIZZLE_128B, CU_TENSOR_MAP_L2_PROMOTION_L2_256B, CU_TENSOR_MAP_FLOAT_OOB_FILL_NONE);
  return m;
}

template <typename... Args>
static void launch(void (*k)(Args...), dim3 grid, dim3 block, size_t smem, bool pdl, Args... args) {
  cudaLaunchConfig_t cfg = {};
  cfg.gridDim = grid; cfg.blockDim = block; cfg.dynamicSmemBytes = smem; cfg.stream = cudaStreamPerThread;
  cudaLaunchAttribute at[1];
  at[0].id = cudaLaunchAttributeProgrammaticStreamSerialization; at[0].val.programmaticStreamSerializationAllowed = 1;
  cfg.attrs = at; cfg.numAttrs = pdl ? 1 : 0;
  cudaLaunchKernelEx(&cfg, k, args...);
}

extern "C" void kernel_launch(void* const* d_in, const int* in_sizes, int n_in, void* d_out, int out_size) {
  const __nv_bfloat16* x = (const __nv_bfloat16*)d_in[0];
  const void* kc = d_in[1]; const void* vc = d_in[2]; const void* wq = d_in[3]; const void* wo = d_in[4];
  const void* w1 = d_in[6]; const void* w2 = d_in[7];
  const __nv_bfloat16* c = (const __nv_bfloat16*)d_in[8];
  const __nv_bfloat16* wm = (const __nv_bfloat16*)d_in[9];

  void* fn = nullptr; cudaDriverEntryPointQueryResult qr;
  cudaGetDriverEntryPoint("cuTensorMapEncodeTiled", &fn, cudaEnableDefault, &qr);
  EncodeFn enc = (EncodeFn)fn;
  void *p_h, *p_oA, *p_h2;
  cudaGetSymbolAddress(&p_h, g_h); cudaGetSymbolAddress(&p_oA, g_oA); cudaGetSymbolAddress(&p_h2, g_h2);
  CUtensorMap tm_h = make_map(enc, p_h, DM, SEQ, 64, 128);
  CUtensorMap tm_wq = make_map(enc, wq, 4096, DM, 64, 64);
  CUtensorMap tm_k = make_map(enc, kc, DH, HKV * SKV, 64, 128);
  CUtensorMap tm_v = make_map(enc, vc, DH, HKV * SKV, 64, 64);
  CUtensorMap tm_wo = make_map(enc, wo, DM, 4096, 64, 64);
  CUtensorMap tm_oA = make_map(enc, p_oA, DH, HKV * SEQ, 64, 128);
  CUtensorMap tm_h2 = make_map(enc, p_h2, DM, SEQ, 64, 128);
  CUtensorMap tm_w1 = make_map(enc, w1, DFF, DM, 64, 64);
  CUtensorMap tm_w2 = make_map(enc, w2, DM, DFF, 64, 64);
  cudaFuncSetAttribute(attn_kernel, cudaFuncAttributeMaxDynamicSharedMemorySize, SM_TOTAL);
  cudaFuncSetAttribute(ffn_kernel, cudaFuncAttributeMaxDynamicSharedMemorySize, SM_TOTAL);

  launch(mod_kernel, dim3(84 + 90), dim3(512), 0, false, c, wm);
  launch(ln1_kernel, dim3(SEQ / 8), dim3(256), 0, true, x);
  launch(attn_kernel, dim3(16, 8), dim3(384), SM_TOTAL, true, tm_h, tm_wq, tm_k, tm_v, tm_wo, tm_oA);
  launch(ln2_kernel, dim3(SEQ / 8), dim3(256), 0, true, x);
  launch(ffn_kernel, dim3(16, 7), dim3(384), SM_TOTAL, true, tm_h2, tm_w1, tm_w2);
  launch(final_kernel, dim3(SEQ * DM / 512), dim3(256), 0, true, (__nv_bfloat16*)d_out);
}
```

```cpp
#include <cuda_runtime.h>
#include <cuda_bf16.h>
#include <cuda.h>
#include <stdint.h>

constexpr int SEQ = 2048, DM = 448, HKV = 8, SKV = 2048, DH = 256, WIN = 512, DFF = 1792;

__device__ __align__(1024) float          g_mod[6 * DM];
__device__ __align__(1024) __nv_bfloat16  g_h[SEQ * DM];
__device__ __align__(1024) __nv_bfloat16  g_oA[HKV * SEQ * DH];
__device__ __align__(1024) float          g_acc1[SEQ * DM];
__device__ __align__(1024) float          g_acc2[SEQ * DM];
__device__ __align__(1024) __nv_bfloat16  g_x1[SEQ * DM];
__device__ __align__(1024) __nv_bfloat16  g_h2[SEQ * DM];

__device__ __forceinline__ uint32_t smem_u32(const void* p) { return (uint32_t)__cvta_generic_to_shared(p); }
__device__ __forceinline__ void mbar_init(uint32_t bar, uint32_t cnt) {
  asm volatile("mbarrier.init.shared::cta.b64 [%0], %1;" ::"r"(bar), "r"(cnt));
}
__device__ __forceinline__ void mbar_expect_tx(uint32_t bar, uint32_t bytes) {
  asm volatile("mbarrier.arrive.expect_tx.shared::cta.b64 _, [%0], %1;" ::"r"(bar), "r"(bytes) : "memory");
}
__device__ __forceinline__ void mbar_arrive(uint32_t bar) {
  asm volatile("mbarrier.arrive.shared::cta.b64 _, [%0];" ::"r"(bar) : "memory");
}
__device__ __forceinline__ void mbar_arrive_remote(uint32_t bar, uint32_t cta) {
  asm volatile("{\n.reg .b32 ra;\nmapa.shared::cluster.u32 ra, %0, %1;\n"
               "mbarrier.arrive.shared::cluster.b64 _, [ra];\n}\n" ::"r"(bar), "r"(cta) : "memory");
}
__device__ __forceinline__ void mbar_wait(uint32_t bar, uint32_t parity) {
  asm volatile("{\n.reg .pred p;\nLAB_WAIT:\n"
               "mbarrier.try_wait.parity.shared::cta.b64 p, [%0], %1, 0x989680;\n"
               "@p bra LAB_DONE;\nbra LAB_WAIT;\nLAB_DONE:\n}\n" ::"r"(bar), "r"(parity) : "memory");
}
__device__ __forceinline__ void mbar_wait_cluster(uint32_t bar, uint32_t parity) {
  asm volatile("{\n.reg .pred p;\nLAB_WAIT:\n"
               "mbarrier.try_wait.parity.acquire.cluster.shared::cta.b64 p, [%0], %1, 0x989680;\n"
               "@p bra LAB_DONE;\nbra LAB_WAIT;\nLAB_DONE:\n}\n" ::"r"(bar), "r"(parity) : "memory");
}
__device__ __forceinline__ void tma_load(uint32_t dst, const CUtensorMap* m, int c0, int c1, uint32_t bar) {
  asm volatile("cp.async.bulk.tensor.2d.shared::cluster.global.mbarrier::complete_tx::bytes [%0], [%1, {%3, %4}], [%2];"
               ::"r"(dst), "l"(m), "r"(bar), "r"(c0), "r"(c1) : "memory");
}
__device__ __forceinline__ void tma_load_mc(uint32_t dst, const CUtensorMap* m, int c0, int c1, uint32_t bar, uint16_t mask) {
  asm volatile("cp.async.bulk.tensor.2d.shared::cluster.global.mbarrier::complete_tx::bytes.multicast::cluster [%0], [%1, {%3, %4}], [%2], %5;"
               ::"r"(dst), "l"(m), "r"(bar), "r"(c0), "r"(c1), "h"(mask) : "memory");
}
__device__ __forceinline__ void cluster_sync_all() {
  asm volatile("barrier.cluster.arrive.release.aligned;\nbarrier.cluster.wait.acquire.aligned;\n" ::: "memory");
}
__device__ __forceinline__ uint32_t cluster_rank() { uint32_t r; asm volatile("mov.u32 %0, %%cluster_ctarank;" : "=r"(r)); return r; }
__device__ __forceinline__ void wg_fence() { asm volatile("wgmma.fence.sync.aligned;" ::: "memory"); }
__device__ __forceinline__ void wg_commit() { asm volatile("wgmma.commit_group.sync.aligned;" ::: "memory"); }
template <int N> __device__ __forceinline__ void wg_wait() { asm volatile("wgmma.wait_group.sync.aligned %0;" ::"n"(N) : "memory"); }
__device__ __forceinline__ void bar_sync(int id, int n) { asm volatile("bar.sync %0, %1;" ::"r"(id), "r"(n) : "memory"); }
__device__ __forceinline__ void bar_arrive(int id, int n) { asm volatile("bar.arrive %0, %1;" ::"r"(id), "r"(n) : "memory"); }
__device__ __forceinline__ void fence_async_smem() { asm volatile("fence.proxy.async.shared::cta;" ::: "memory"); }
__device__ __forceinline__ void fence_async() { asm volatile("fence.proxy.async;" ::: "memory"); }
__device__ __forceinline__ uint64_t mk_desc(uint32_t saddr, uint32_t lbo, uint32_t sbo) {
  return (uint64_t)((saddr & 0x3FFFF) >> 4) | ((uint64_t)(lbo >> 4) << 16) | ((uint64_t)(sbo >> 4) << 32) | (1ull << 62);
}
__device__ __forceinline__ uint32_t pack_bf16(float lo, float hi) {
  uint32_t r; asm("cvt.rn.bf16x2.f32 %0, %1, %2;" : "=r"(r) : "f"(hi), "f"(lo)); return r;
}
__device__ __forceinline__ float bf_lo(uint32_t v) { return __uint_as_float(v << 16); }
__device__ __forceinline__ float bf_hi(uint32_t v) { return __uint_as_float(v & 0xFFFF0000u); }
__device__ __forceinline__ float rbf(float x) { return __bfloat162float(__float2bfloat16_rn(x)); }
__device__ __forceinline__ float ex2(float x) { float r; asm("ex2.approx.ftz.f32 %0, %1;" : "=f"(r) : "f"(x)); return r; }
__device__ __forceinline__ void red_add_v2(float* p, float a, float b) {
  asm volatile("red.global.add.v2.f32 [%0], {%1, %2};" ::"l"(p), "f"(a), "f"(b) : "memory");
}
__device__ __forceinline__ void pdl_wait() { asm volatile("griddepcontrol.wait;" ::: "memory"); }
__device__ __forceinline__ void pdl_launch() { asm volatile("griddepcontrol.launch_dependents;" ::: "memory"); }

__device__ __forceinline__ void wgmma_m64n256k16_ss_tb(float (&d)[128], uint64_t da, uint64_t db, int sc) {
  asm volatile("{\n.reg .pred p;\nsetp.ne.b32 p, %130, 0;\n"
    "wgmma.mma_async.sync.aligned.m64n256k16.f32.bf16.bf16 {%0, %1, %2, %3, %4, %5, %6, %7, %8, %9, %10, %11, %12, %13, %14, %15, %16, %17, %18, %19, %20, %21, %22, %23, %24, %25, %26, %27, %28, %29, %30, %31, %32, %33, %34, %35, %36, %37, %38, %39, %40, %41, %42, %43, %44, %45, %46, %47, %48, %49, %50, %51, %52, %53, %54, %55, %56, %57, %58, %59, %60, %61, %62, %63, %64, %65, %66, %67, %68, %69, %70, %71, %72, %73, %74, %75, %76, %77, %78, %79, %80, %81, %82, %83, %84, %85, %86, %87, %88, %89, %90, %91, %92, %93, %94, %95, %96, %97, %98, %99, %100, %101, %102, %103, %104, %105, %106, %107, %108, %109, %110, %111, %112, %113, %114, %115, %116, %117, %118, %119, %120, %121, %122, %123, %124, %125, %126, %127}, %128, %129, p, 1, 1, 0, 1;\n}\n"
    : "+f"(d[0]), "+f"(d[1]), "+f"(d[2]), "+f"(d[3]), "+f"(d[4]), "+f"(d[5]), "+f"(d[6]), "+f"(d[7]), "+f"(d[8]), "+f"(d[9]), "+f"(d[10]), "+f"(d[11]), "+f"(d[12]), "+f"(d[13]), "+f"(d[14]), "+f"(d[15]), "+f"(d[16]), "+f"(d[17]), "+f"(d[18]), "+f"(d[19]), "+f"(d[20]), "+f"(d[21]), "+f"(d[22]), "+f"(d[23]), "+f"(d[24]), "+f"(d[25]), "+f"(d[26]), "+f"(d[27]), "+f"(d[28]), "+f"(d[29]), "+f"(d[30]), "+f"(d[31]), "+f"(d[32]), "+f"(d[33]), "+f"(d[34]), "+f"(d[35]), "+f"(d[36]), "+f"(d[37]), "+f"(d[38]), "+f"(d[39]), "+f"(d[40]), "+f"(d[41]), "+f"(d[42]), "+f"(d[43]), "+f"(d[44]), "+f"(d[45]), "+f"(d[46]), "+f"(d[47]), "+f"(d[48]), "+f"(d[49]), "+f"(d[50]), "+f"(d[51]), "+f"(d[52]), "+f"(d[53]), "+f"(d[54]), "+f"(d[55]), "+f"(d[56]), "+f"(d[57]), "+f"(d[58]), "+f"(d[59]), "+f"(d[60]), "+f"(d[61]), "+f"(d[62]), "+f"(d[63]), "+f"(d[64]), "+f"(d[65]), "+f"(d[66]), "+f"(d[67]), "+f"(d[68]), "+f"(d[69]), "+f"(d[70]), "+f"(d[71]), "+f"(d[72]), "+f"(d[73]), "+f"(d[74]), "+f"(d[75]), "+f"(d[76]), "+f"(d[77]), "+f"(d[78]), "+f"(d[79]), "+f"(d[80]), "+f"(d[81]), "+f"(d[82]), "+f"(d[83]), "+f"(d[84]), "+f"(d[85]), "+f"(d[86]), "+f"(d[87]), "+f"(d[88]), "+f"(d[89]), "+f"(d[90]), "+f"(d[91]), "+f"(d[92]), "+f"(d[93]), "+f"(d[94]), "+f"(d[95]), "+f"(d[96]), "+f"(d[97]), "+f"(d[98]), "+f"(d[99]), "+f"(d[100]), "+f"(d[101]), "+f"(d[102]), "+f"(d[103]), "+f"(d[104]), "+f"(d[105]), "+f"(d[106]), "+f"(d[107]), "+f"(d[108]), "+f"(d[109]), "+f"(d[110]), "+f"(d[111]), "+f"(d[112]), "+f"(d[113]), "+f"(d[114]), "+f"(d[115]), "+f"(d[116]), "+f"(d[117]), "+f"(d[118]), "+f"(d[119]), "+f"(d[120]), "+f"(d[121]), "+f"(d[122]), "+f"(d[123]), "+f"(d[124]), "+f"(d[125]), "+f"(d[126]), "+f"(d[127])
    : "l"(da), "l"(db), "r"(sc));
}
__device__ __forceinline__ void wgmma_m64n128k16_ss(float (&d)[64], uint64_t da, uint64_t db, int sc) {
  asm volatile("{\n.reg .pred p;\nsetp.ne.b32 p, %66, 0;\n"
    "wgmma.mma_async.sync.aligned.m64n128k16.f32.bf16.bf16 {%0, %1, %2, %3, %4, %5, %6, %7, %8, %9, %10, %11, %12, %13, %14, %15, %16, %17, %18, %19, %20, %21, %22, %23, %24, %25, %26, %27, %28, %29, %30, %31, %32, %33, %34, %35, %36, %37, %38, %39, %40, %41, %42, %43, %44, %45, %46, %47, %48, %49, %50, %51, %52, %53, %54, %55, %56, %57, %58, %59, %60, %61, %62, %63}, %64, %65, p, 1, 1, 0, 0;\n}\n"
    : "+f"(d[0]), "+f"(d[1]), "+f"(d[2]), "+f"(d[3]), "+f"(d[4]), "+f"(d[5]), "+f"(d[6]), "+f"(d[7]), "+f"(d[8]), "+f"(d[9]), "+f"(d[10]), "+f"(d[11]), "+f"(d[12]), "+f"(d[13]), "+f"(d[14]), "+f"(d[15]), "+f"(d[16]), "+f"(d[17]), "+f"(d[18]), "+f"(d[19]), "+f"(d[20]), "+f"(d[21]), "+f"(d[22]), "+f"(d[23]), "+f"(d[24]), "+f"(d[25]), "+f"(d[26]), "+f"(d[27]), "+f"(d[28]), "+f"(d[29]), "+f"(d[30]), "+f"(d[31]), "+f"(d[32]), "+f"(d[33]), "+f"(d[34]), "+f"(d[35]), "+f"(d[36]), "+f"(d[37]), "+f"(d[38]), "+f"(d[39]), "+f"(d[40]), "+f"(d[41]), "+f"(d[42]), "+f"(d[43]), "+f"(d[44]), "+f"(d[45]), "+f"(d[46]), "+f"(d[47]), "+f"(d[48]), "+f"(d[49]), "+f"(d[50]), "+f"(d[51]), "+f"(d[52]), "+f"(d[53]), "+f"(d[54]), "+f"(d[55]), "+f"(d[56]), "+f"(d[57]), "+f"(d[58]), "+f"(d[59]), "+f"(d[60]), "+f"(d[61]), "+f"(d[62]), "+f"(d[63])
    : "l"(da), "l"(db), "r"(sc));
}
__device__ __forceinline__ void wgmma_m64n256k16_rs_tb(float (&d)[128], uint32_t a0, uint32_t a1, uint32_t a2, uint32_t a3, uint64_t db, int sc) {
  asm volatile("{\n.reg .pred p;\nsetp.ne.b32 p, %133, 0;\n"
    "wgmma.mma_async.sync.aligned.m64n256k16.f32.bf16.bf16 {%0, %1, %2, %3, %4, %5, %6, %7, %8, %9, %10, %11, %12, %13, %14, %15, %16, %17, %18, %19, %20, %21, %22, %23, %24, %25, %26, %27, %28, %29, %30, %31, %32, %33, %34, %35, %36, %37, %38, %39, %40, %41, %42, %43, %44, %45, %46, %47, %48, %49, %50, %51, %52, %53, %54, %55, %56, %57, %58, %59, %60, %61, %62, %63, %64, %65, %66, %67, %68, %69, %70, %71, %72, %73, %74, %75, %76, %77, %78, %79, %80, %81, %82, %83, %84, %85, %86, %87, %88, %89, %90, %91, %92, %93, %94, %95, %96, %97, %98, %99, %100, %101, %102, %103, %104, %105, %106, %107, %108, %109, %110, %111, %112, %113, %114, %115, %116, %117, %118, %119, %120, %121, %122, %123, %124, %125, %126, %127}, {%128, %129, %130, %131}, %132, p, 1, 1, 1;\n}\n"
    : "+f"(d[0]), "+f"(d[1]), "+f"(d[2]), "+f"(d[3]), "+f"(d[4]), "+f"(d[5]), "+f"(d[6]), "+f"(d[7]), "+f"(d[8]), "+f"(d[9]), "+f"(d[10]), "+f"(d[11]), "+f"(d[12]), "+f"(d[13]), "+f"(d[14]), "+f"(d[15]), "+f"(d[16]), "+f"(d[17]), "+f"(d[18]), "+f"(d[19]), "+f"(d[20]), "+f"(d[21]), "+f"(d[22]), "+f"(d[23]), "+f"(d[24]), "+f"(d[25]), "+f"(d[26]), "+f"(d[27]), "+f"(d[28]), "+f"(d[29]), "+f"(d[30]), "+f"(d[31]), "+f"(d[32]), "+f"(d[33]), "+f"(d[34]), "+f"(d[35]), "+f"(d[36]), "+f"(d[37]), "+f"(d[38]), "+f"(d[39]), "+f"(d[40]), "+f"(d[41]), "+f"(d[42]), "+f"(d[43]), "+f"(d[44]), "+f"(d[45]), "+f"(d[46]), "+f"(d[47]), "+f"(d[48]), "+f"(d[49]), "+f"(d[50]), "+f"(d[51]), "+f"(d[52]), "+f"(d[53]), "+f"(d[54]), "+f"(d[55]), "+f"(d[56]), "+f"(d[57]), "+f"(d[58]), "+f"(d[59]), "+f"(d[60]), "+f"(d[61]), "+f"(d[62]), "+f"(d[63]), "+f"(d[64]), "+f"(d[65]), "+f"(d[66]), "+f"(d[67]), "+f"(d[68]), "+f"(d[69]), "+f"(d[70]), "+f"(d[71]), "+f"(d[72]), "+f"(d[73]), "+f"(d[74]), "+f"(d[75]), "+f"(d[76]), "+f"(d[77]), "+f"(d[78]), "+f"(d[79]), "+f"(d[80]), "+f"(d[81]), "+f"(d[82]), "+f"(d[83]), "+f"(d[84]), "+f"(d[85]), "+f"(d[86]), "+f"(d[87]), "+f"(d[88]), "+f"(d[89]), "+f"(d[90]), "+f"(d[91]), "+f"(d[92]), "+f"(d[93]), "+f"(d[94]), "+f"(d[95]), "+f"(d[96]), "+f"(d[97]), "+f"(d[98]), "+f"(d[99]), "+f"(d[100]), "+f"(d[101]), "+f"(d[102]), "+f"(d[103]), "+f"(d[104]), "+f"(d[105]), "+f"(d[106]), "+f"(d[107]), "+f"(d[108]), "+f"(d[109]), "+f"(d[110]), "+f"(d[111]), "+f"(d[112]), "+f"(d[113]), "+f"(d[114]), "+f"(d[115]), "+f"(d[116]), "+f"(d[117]), "+f"(d[118]), "+f"(d[119]), "+f"(d[120]), "+f"(d[121]), "+f"(d[122]), "+f"(d[123]), "+f"(d[124]), "+f"(d[125]), "+f"(d[126]), "+f"(d[127])
    : "r"(a0), "r"(a1), "r"(a2), "r"(a3), "l"(db), "r"(sc));
}
__device__ __forceinline__ void wgmma_m64n128k16_ss_tb(float (&d)[64], uint64_t da, uint64_t db, int sc) {
  asm volatile("{\n.reg .pred p;\nsetp.ne.b32 p, %66, 0;\n"
    "wgmma.mma_async.sync.aligned.m64n128k16.f32.bf16.bf16 {%0, %1, %2, %3, %4, %5, %6, %7, %8, %9, %10, %11, %12, %13, %14, %15, %16, %17, %18, %19, %20, %21, %22, %23, %24, %25, %26, %27, %28, %29, %30, %31, %32, %33, %34, %35, %36, %37, %38, %39, %40, %41, %42, %43, %44, %45, %46, %47, %48, %49, %50, %51, %52, %53, %54, %55, %56, %57, %58, %59, %60, %61, %62, %63}, %64, %65, p, 1, 1, 0, 1;\n}\n"
    : "+f"(d[0]), "+f"(d[1]), "+f"(d[2]), "+f"(d[3]), "+f"(d[4]), "+f"(d[5]), "+f"(d[6]), "+f"(d[7]), "+f"(d[8]), "+f"(d[9]), "+f"(d[10]), "+f"(d[11]), "+f"(d[12]), "+f"(d[13]), "+f"(d[14]), "+f"(d[15]), "+f"(d[16]), "+f"(d[17]), "+f"(d[18]), "+f"(d[19]), "+f"(d[20]), "+f"(d[21]), "+f"(d[22]), "+f"(d[23]), "+f"(d[24]), "+f"(d[25]), "+f"(d[26]), "+f"(d[27]), "+f"(d[28]), "+f"(d[29]), "+f"(d[30]), "+f"(d[31]), "+f"(d[32]), "+f"(d[33]), "+f"(d[34]), "+f"(d[35]), "+f"(d[36]), "+f"(d[37]), "+f"(d[38]), "+f"(d[39]), "+f"(d[40]), "+f"(d[41]), "+f"(d[42]), "+f"(d[43]), "+f"(d[44]), "+f"(d[45]), "+f"(d[46]), "+f"(d[47]), "+f"(d[48]), "+f"(d[49]), "+f"(d[50]), "+f"(d[51]), "+f"(d[52]), "+f"(d[53]), "+f"(d[54]), "+f"(d[55]), "+f"(d[56]), "+f"(d[57]), "+f"(d[58]), "+f"(d[59]), "+f"(d[60]), "+f"(d[61]), "+f"(d[62]), "+f"(d[63])
    : "l"(da), "l"(db), "r"(sc));
}
__device__ __forceinline__ void wgmma_m64n128k16_rs_tb(float (&d)[64], uint32_t a0, uint32_t a1, uint32_t a2, uint32_t a3, uint64_t db, int sc) {
  asm volatile("{\n.reg .pred p;\nsetp.ne.b32 p, %69, 0;\n"
    "wgmma.mma_async.sync.aligned.m64n128k16.f32.bf16.bf16 {%0, %1, %2, %3, %4, %5, %6, %7, %8, %9, %10, %11, %12, %13, %14, %15, %16, %17, %18, %19, %20, %21, %22, %23, %24, %25, %26, %27, %28, %29, %30, %31, %32, %33, %34, %35, %36, %37, %38, %39, %40, %41, %42, %43, %44, %45, %46, %47, %48, %49, %50, %51, %52, %53, %54, %55, %56, %57, %58, %59, %60, %61, %62, %63}, {%64, %65, %66, %67}, %68, p, 1, 1, 1;\n}\n"
    : "+f"(d[0]), "+f"(d[1]), "+f"(d[2]), "+f"(d[3]), "+f"(d[4]), "+f"(d[5]), "+f"(d[6]), "+f"(d[7]), "+f"(d[8]), "+f"(d[9]), "+f"(d[10]), "+f"(d[11]), "+f"(d[12]), "+f"(d[13]), "+f"(d[14]), "+f"(d[15]), "+f"(d[16]), "+f"(d[17]), "+f"(d[18]), "+f"(d[19]), "+f"(d[20]), "+f"(d[21]), "+f"(d[22]), "+f"(d[23]), "+f"(d[24]), "+f"(d[25]), "+f"(d[26]), "+f"(d[27]), "+f"(d[28]), "+f"(d[29]), "+f"(d[30]), "+f"(d[31]), "+f"(d[32]), "+f"(d[33]), "+f"(d[34]), "+f"(d[35]), "+f"(d[36]), "+f"(d[37]), "+f"(d[38]), "+f"(d[39]), "+f"(d[40]), "+f"(d[41]), "+f"(d[42]), "+f"(d[43]), "+f"(d[44]), "+f"(d[45]), "+f"(d[46]), "+f"(d[47]), "+f"(d[48]), "+f"(d[49]), "+f"(d[50]), "+f"(d[51]), "+f"(d[52]), "+f"(d[53]), "+f"(d[54]), "+f"(d[55]), "+f"(d[56]), "+f"(d[57]), "+f"(d[58]), "+f"(d[59]), "+f"(d[60]), "+f"(d[61]), "+f"(d[62]), "+f"(d[63])
    : "r"(a0), "r"(a1), "r"(a2), "r"(a3), "l"(db), "r"(sc));
}
__device__ __forceinline__ void wgmma_m64n64k16_ss_tb(float (&d)[32], uint64_t da, uint64_t db, int sc) {
  asm volatile("{\n.reg .pred p;\nsetp.ne.b32 p, %34, 0;\n"
    "wgmma.mma_async.sync.aligned.m64n64k16.f32.bf16.bf16 {%0, %1, %2, %3, %4, %5, %6, %7, %8, %9, %10, %11, %12, %13, %14, %15, %16, %17, %18, %19, %20, %21, %22, %23, %24, %25, %26, %27, %28, %29, %30, %31}, %32, %33, p, 1, 1, 0, 1;\n}\n"
    : "+f"(d[0]), "+f"(d[1]), "+f"(d[2]), "+f"(d[3]), "+f"(d[4]), "+f"(d[5]), "+f"(d[6]), "+f"(d[7]), "+f"(d[8]), "+f"(d[9]), "+f"(d[10]), "+f"(d[11]), "+f"(d[12]), "+f"(d[13]), "+f"(d[14]), "+f"(d[15]), "+f"(d[16]), "+f"(d[17]), "+f"(d[18]), "+f"(d[19]), "+f"(d[20]), "+f"(d[21]), "+f"(d[22]), "+f"(d[23]), "+f"(d[24]), "+f"(d[25]), "+f"(d[26]), "+f"(d[27]), "+f"(d[28]), "+f"(d[29]), "+f"(d[30]), "+f"(d[31])
    : "l"(da), "l"(db), "r"(sc));
}
__device__ __forceinline__ void wgmma_m64n64k16_rs_tb(float (&d)[32], uint32_t a0, uint32_t a1, uint32_t a2, uint32_t a3, uint64_t db, int sc) {
  asm volatile("{\n.reg .pred p;\nsetp.ne.b32 p, %37, 0;\n"
    "wgmma.mma_async.sync.aligned.m64n64k16.f32.bf16.bf16 {%0, %1, %2, %3, %4, %5, %6, %7, %8, %9, %10, %11, %12, %13, %14, %15, %16, %17, %18, %19, %20, %21, %22, %23, %24, %25, %26, %27, %28, %29, %30, %31}, {%32, %33, %34, %35}, %36, p, 1, 1, 1;\n}\n"
    : "+f"(d[0]), "+f"(d[1]), "+f"(d[2]), "+f"(d[3]), "+f"(d[4]), "+f"(d[5]), "+f"(d[6]), "+f"(d[7]), "+f"(d[8]), "+f"(d[9]), "+f"(d[10]), "+f"(d[11]), "+f"(d[12]), "+f"(d[13]), "+f"(d[14]), "+f"(d[15]), "+f"(d[16]), "+f"(d[17]), "+f"(d[18]), "+f"(d[19]), "+f"(d[20]), "+f"(d[21]), "+f"(d[22]), "+f"(d[23]), "+f"(d[24]), "+f"(d[25]), "+f"(d[26]), "+f"(d[27]), "+f"(d[28]), "+f"(d[29]), "+f"(d[30]), "+f"(d[31])
    : "r"(a0), "r"(a1), "r"(a2), "r"(a3), "l"(db), "r"(sc));
}
__device__ __forceinline__ void wgmma_m64n192k16_ss_tb(float (&d)[128], uint64_t da, uint64_t db, int sc) {
  asm volatile("{\n.reg .pred p;\nsetp.ne.b32 p, %98, 0;\n"
    "wgmma.mma_async.sync.aligned.m64n192k16.f32.bf16.bf16 {%0, %1, %2, %3, %4, %5, %6, %7, %8, %9, %10, %11, %12, %13, %14, %15, %16, %17, %18, %19, %20, %21, %22, %23, %24, %25, %26, %27, %28, %29, %30, %31, %32, %33, %34, %35, %36, %37, %38, %39, %40, %41, %42, %43, %44, %45, %46, %47, %48, %49, %50, %51, %52, %53, %54, %55, %56, %57, %58, %59, %60, %61, %62, %63, %64, %65, %66, %67, %68, %69, %70, %71, %72, %73, %74, %75, %76, %77, %78, %79, %80, %81, %82, %83, %84, %85, %86, %87, %88, %89, %90, %91, %92, %93, %94, %95}, %96, %97, p, 1, 1, 0, 1;\n}\n"
    : "+f"(d[0]), "+f"(d[1]), "+f"(d[2]), "+f"(d[3]), "+f"(d[4]), "+f"(d[5]), "+f"(d[6]), "+f"(d[7]), "+f"(d[8]), "+f"(d[9]), "+f"(d[10]), "+f"(d[11]), "+f"(d[12]), "+f"(d[13]), "+f"(d[14]), "+f"(d[15]), "+f"(d[16]), "+f"(d[17]), "+f"(d[18]), "+f"(d[19]), "+f"(d[20]), "+f"(d[21]), "+f"(d[22]), "+f"(d[23]), "+f"(d[24]), "+f"(d[25]), "+f"(d[26]), "+f"(d[27]), "+f"(d[28]), "+f"(d[29]), "+f"(d[30]), "+f"(d[31]), "+f"(d[32]), "+f"(d[33]), "+f"(d[34]), "+f"(d[35]), "+f"(d[36]), "+f"(d[37]), "+f"(d[38]), "+f"(d[39]), "+f"(d[40]), "+f"(d[41]), "+f"(d[42]), "+f"(d[43]), "+f"(d[44]), "+f"(d[45]), "+f"(d[46]), "+f"(d[47]), "+f"(d[48]), "+f"(d[49]), "+f"(d[50]), "+f"(d[51]), "+f"(d[52]), "+f"(d[53]), "+f"(d[54]), "+f"(d[55]), "+f"(d[56]), "+f"(d[57]), "+f"(d[58]), "+f"(d[59]), "+f"(d[60]), "+f"(d[61]), "+f"(d[62]), "+f"(d[63]), "+f"(d[64]), "+f"(d[65]), "+f"(d[66]), "+f"(d[67]), "+f"(d[68]), "+f"(d[69]), "+f"(d[70]), "+f"(d[71]), "+f"(d[72]), "+f"(d[73]), "+f"(d[74]), "+f"(d[75]), "+f"(d[76]), "+f"(d[77]), "+f"(d[78]), "+f"(d[79]), "+f"(d[80]), "+f"(d[81]), "+f"(d[82]), "+f"(d[83]), "+f"(d[84]), "+f"(d[85]), "+f"(d[86]), "+f"(d[87]), "+f"(d[88]), "+f"(d[89]), "+f"(d[90]), "+f"(d[91]), "+f"(d[92]), "+f"(d[93]), "+f"(d[94]), "+f"(d[95])
    : "l"(da), "l"(db), "r"(sc));
}

#define TM(id)
#define GT_MIN(i)
#define GT_MAX(i)

constexpr int NS = 5;
constexpr uint32_t STG = 32768;
constexpr uint32_t SM_Q = 0;
constexpr uint32_t SM_RING = 65536;
constexpr uint32_t SM_BAR = SM_RING + NS * STG;
constexpr uint32_t SM_TOTAL = SM_BAR + 256 + 1024;

struct Ring {
  uint32_t base, full0, empty0, st, ph, nst, stg;
  __device__ __forceinline__ void init(uint32_t sb) { base = sb + SM_RING; full0 = sb + SM_BAR; empty0 = sb + SM_BAR + 64; st = 0; ph = 0; nst = NS; stg = STG; }
  __device__ __forceinline__ uint32_t phase() const { return (ph >> st) & 1; }
  __device__ __forceinline__ uint32_t buf() const { return base + st * stg; }
  __device__ __forceinline__ uint32_t full() const { return full0 + st * 8; }
  __device__ __forceinline__ uint32_t empty() const { return empty0 + st * 8; }
  __device__ __forceinline__ void next() { ph ^= 1u << st; st = (st + 1 >= nst) ? 0 : st + 1; }
  __device__ __forceinline__ void shrink() { nst = NS - 1; if (st >= nst) st = 0; }
  __device__ __forceinline__ uint32_t acquire(uint32_t bytes) {
    mbar_wait(empty(), phase() ^ 1); mbar_expect_tx(full(), bytes); return buf();
  }
  __device__ __forceinline__ uint32_t wait() { mbar_wait(full(), phase()); return buf(); }
};
template <int CL = 2>
__device__ __forceinline__ void ring_release(uint32_t empty_bar, int lane) {
  __syncwarp();
  if (lane < CL) mbar_arrive_remote(empty_bar, (uint32_t)lane);
}

template <int CL>
__device__ __forceinline__ void gemm_k448_n256(Ring& r, float (&acc)[128], int wg, int lane) {
  uint32_t hb = 0, hrel = 0, prel = 0, phrel = 0;
#pragma unroll
  for (int c = 0; c < 7; ++c) {
    if ((c & 1) == 0) { hb = r.wait(); hrel = r.empty(); r.next(); }
    uint32_t wb = r.wait(); uint32_t wrel = r.empty(); r.next();
    uint64_t da = mk_desc(hb + (c & 1) * 16384 + wg * 8192, 16, 1024);
    uint64_t db = mk_desc(wb, 8192, 1024);
    wg_fence();
#pragma unroll
    for (int k = 0; k < 4; ++k) wgmma_m64n256k16_ss_tb(acc, da + k * 2, db + k * 128, (c | k) != 0);
    wg_commit();
    if (c > 0) {
      wg_wait<1>();
      ring_release<CL>(prel, lane);
      if ((c & 1) == 0) ring_release<CL>(phrel, lane);
    }
    prel = wrel; phrel = hrel;
  }
  wg_wait<0>();
  ring_release<CL>(prel, lane); ring_release<CL>(phrel, lane);
}

template <bool RELU>
__device__ __forceinline__ void store_tile_bf16(uint32_t base, const float (&acc)[128], int rloc, int t4) {
  uint32_t row0 = base + rloc * 128, row1 = row0 + 8 * 128;
  uint32_t sw = (uint32_t)(rloc & 7);
#pragma unroll
  for (int j = 0; j < 32; ++j) {
    uint32_t off = (uint32_t)(j >> 3) * 16384 + ((((uint32_t)j & 7) ^ sw) << 4) + t4 * 4;
    float a = acc[4 * j], b = acc[4 * j + 1], c = acc[4 * j + 2], d = acc[4 * j + 3];
    if (RELU) { a = fmaxf(a, 0.f); b = fmaxf(b, 0.f); c = fmaxf(c, 0.f); d = fmaxf(d, 0.f); }
    asm volatile("st.shared.b32 [%0], %1;" ::"r"(row0 + off), "r"(pack_bf16(a, b)) : "memory");
    asm volatile("st.shared.b32 [%0], %1;" ::"r"(row1 + off), "r"(pack_bf16(c, d)) : "memory");
  }
}

template <int NJ, int OFF = 0, int SZ = 64, bool WAIT = true>
__device__ __forceinline__ void red_rows(uint32_t stg, const CUtensorMap* tm, int row0, int col0, const float (&a)[SZ], int sel, int lane) {
  asm volatile("" : "+r"(stg), "+r"(lane));
  if (WAIT) {
    if (lane == 0) asm volatile("cp.async.bulk.wait_group.read 0;" ::: "memory");
    __syncwarp();
  }
  const uint32_t g = lane >> 2, t4 = lane & 3;
  const uint32_t wbase = stg + g * 128 + (t4 & 1) * 8;
#pragma unroll
  for (int j = 0; j < NJ; ++j)
    asm volatile("st.shared.v2.f32 [%0], {%1, %2};" ::"r"(wbase + (j >> 2) * 1024 + ((((j & 3) * 2 + (t4 >> 1)) ^ g) << 4)),
                 "f"(a[OFF + 4 * j + sel]), "f"(a[OFF + 4 * j + sel + 1]) : "memory");
  fence_async_smem();
  __syncwarp();
  if (lane == 0) {
#pragma unroll
    for (int b = 0; b < NJ / 4; ++b)
      asm volatile("cp.reduce.async.bulk.tensor.2d.global.shared::cta.add.tile.bulk_group [%0, {%2, %3}], [%1];"
                   ::"l"(tm), "r"(stg + b * 1024), "r"(col0 + b * 32), "r"(row0) : "memory");
    asm volatile("cp.async.bulk.commit_group;" ::: "memory");
  }
}

template <int NSM, int NRG, int CL>
__device__ __forceinline__ void out_proj(Ring& r, const uint32_t (&ob)[64], uint32_t abase,
                                         const CUtensorMap* tm, int roww, uint32_t stg, int lane) {
  constexpr int NST = (NSM + NRG) / 2;
  uint32_t prel = 0;
  float accA[64], accB[64];
  float(&cur32)[32] = *reinterpret_cast<float(*)[32]>(&accB[0]);
#pragma unroll
  for (int pass = 0; pass < 4; ++pass) {
    float(&cur)[64] = (pass & 1) ? accB : accA;
    float(&prv)[64] = (pass & 1) ? accA : accB;
#pragma unroll
    for (int st = 0; st < NST; ++st) {
      uint32_t wb = r.wait(); uint32_t rel = r.empty(); r.next();
      asm volatile("" : "+r"(abase));
      wg_fence();
#pragma unroll
      for (int cc = 0; cc < 2; ++cc) {
        const int c = 2 * st + cc;
#pragma unroll
        for (int k = 0; k < 4; ++k) {
          const int sc = (c | k) != 0;
          if (pass < 3) {
            uint64_t db = mk_desc(wb + cc * 16384 + k * 2048, 8192, 1024);
            if (c < NSM) wgmma_m64n128k16_ss_tb(cur, mk_desc(abase + c * 16384 + k * 32, 16, 1024), db, sc);
            else { const int o = (c - NSM) * 16 + 4 * k; wgmma_m64n128k16_rs_tb(cur, ob[o], ob[o + 1], ob[o + 2], ob[o + 3], db, sc); }
          } else {
            uint64_t db = mk_desc(wb + cc * 8192 + k * 2048, 8192, 1024);
            if (c < NSM) wgmma_m64n64k16_ss_tb(cur32, mk_desc(abase + c * 16384 + k * 32, 16, 1024), db, sc);
            else { const int o = (c - NSM) * 16 + 4 * k; wgmma_m64n64k16_rs_tb(cur32, ob[o], ob[o + 1], ob[o + 2], ob[o + 3], db, sc); }
          }
        }
      }
      wg_commit();
      if (pass | st) { wg_wait<1>(); ring_release<CL>(prel, lane); }
      prel = rel;
      if (pass > 0) {
        if (st == 0) red_rows<16>(stg, tm, roww, (pass - 1) * 128, prv, 0, lane);
        if (st == NST / 2) red_rows<16>(stg, tm, roww + 8, (pass - 1) * 128, prv, 2, lane);
      }
    }
  }
  wg_wait<0>(); ring_release<CL>(prel, lane);
  red_rows<8>(stg, tm, roww, 384, accB, 0, lane);
  red_rows<8>(stg, tm, roww + 8, 384, accB, 2, lane);
  if (lane == 0) asm volatile("cp.async.bulk.wait_group 0;" ::: "memory");
}
template <int CL>
__device__ __forceinline__ void out_proj_loads(Ring& r, const CUtensorMap* tm, int krow0, int nch, uint32_t rank) {
  r.shrink();
  constexpr uint16_t MASK = (1 << CL) - 1;
  for (int pass = 0; pass < 4; ++pass)
    for (int st = 0; st < nch / 2; ++st) {
      if (pass < 3) {
        uint32_t b = r.acquire(32768);
        for (int x = 0; x < 4 / CL; ++x) {
          const int bx = rank * (4 / CL) + x;
          tma_load_mc(b + bx * 8192, tm, pass * 128 + (bx & 1) * 64, krow0 + (2 * st + (bx >> 1)) * 64, r.full(), MASK);
        }
      } else {
        uint32_t b = r.acquire(16384);
        if (CL == 1) { for (int x = 0; x < 2; ++x) tma_load_mc(b + x * 8192, tm, 384, krow0 + (2 * st + x) * 64, r.full(), MASK); }
        else if (rank < 2) tma_load_mc(b + rank * 8192, tm, 384, krow0 + (2 * st + rank) * 64, r.full(), MASK);
      }
      r.next();
    }
}

#define ACL 2
__global__ void __cluster_dims__(ACL, 1, 1) __launch_bounds__(384, 1)
attn_kernel(const __grid_constant__ CUtensorMap tm_h, const __grid_constant__ CUtensorMap tm_wq,
            const __grid_constant__ CUtensorMap tm_k, const __grid_constant__ CUtensorMap tm_v,
            const __grid_constant__ CUtensorMap tm_wo, const __grid_constant__ CUtensorMap tm_oA,
            const __grid_constant__ CUtensorMap tm_oAs, const __grid_constant__ CUtensorMap tm_acc) {
  extern __shared__ uint8_t smem_raw[];
  const uint32_t sb = (smem_u32(smem_raw) + 1023) & ~1023u;
  const int tid = threadIdx.x, wg = tid >> 7, lane = tid & 31;
  const int qt = blockIdx.x, kvh = blockIdx.y;
  const uint32_t rank = cluster_rank();
  Ring r; r.init(sb);
  const uint32_t bar_oA = sb + SM_BAR + 128, bar_oAf = sb + SM_BAR + 136;
  if (tid == 0) {
    for (int i = 0; i < NS; ++i) { mbar_init(r.full0 + 8 * i, 1); mbar_init(r.empty0 + 8 * i, 8 * ACL); }
    mbar_init(bar_oA, 256); mbar_init(bar_oAf, 1);
    asm volatile("fence.mbarrier_init.release.cluster;" ::: "memory");
  }
  cluster_sync_all();
  pdl_wait();
  GT_MIN(4);

  if (wg == 2) {
    asm volatile("setmaxnreg.dec.sync.aligned.u32 24;");
    if (tid == 256) {
      const int krow0 = kvh * SKV + (SKV - WIN);
      for (int hh = 0; hh < 2; ++hh) {
        const int head = kvh * 2 + hh;
        for (int p = 0; p < 4; ++p) {
          int nc = (p < 3) ? 2 : 1;
          uint32_t b = r.acquire(nc * 16384);
          for (int c = 0; c < nc; ++c) tma_load(b + c * 16384, &tm_h, (2 * p + c) * 64, qt * 128, r.full());
          r.next();
          for (int c = 0; c < nc; ++c) {
            b = r.acquire(32768);
            for (int x = 0; x < 4 / ACL; ++x) {
              int bx = rank * 2 + x;
              tma_load_mc(b + bx * 8192, &tm_wq, head * 256 + bx * 64, (2 * p + c) * 64, r.full(), (1 << ACL) - 1);
            }
            r.next();
          }
        }
        for (int t = 0; t < 4; ++t) {
          for (int hf = 0; hf < 2; ++hf) {
            uint32_t b = r.acquire(32768);
            for (int x = 0; x < 2 / ACL; ++x)
              tma_load_mc(b + (rank + x) * 16384, &tm_k, (2 * hf + rank + x) * 64, krow0 + t * 128, r.full(), (1 << ACL) - 1);
            r.next();
          }
          for (int hf = 0; hf < 2; ++hf) {
            uint32_t b = r.acquire(32768);
            for (int x = 0; x < 4 / ACL; ++x) {
              int bx = rank * 2 + x;
              tma_load_mc(b + bx * 8192, &tm_v, bx * 64, krow0 + t * 128 + hf * 64, r.full(), (1 << ACL) - 1);
            }
            r.next();
          }
        }
      }
      mbar_wait(bar_oA, 0);
      mbar_expect_tx(bar_oAf, 65536);
      for (int c = 0; c < 4; ++c) tma_load(sb + SM_Q + c * 16384, &tm_oA, c * 64, kvh * SEQ + qt * 128, bar_oAf);
      out_proj_loads<ACL>(r, &tm_wo, kvh * 512, 8, rank);
    }
  } else {
    asm volatile("setmaxnreg.inc.sync.aligned.u32 240;");
    const int warp = (tid >> 5) & 3, g = lane >> 2, t4 = lane & 3;
    const int rloc = wg * 64 + warp * 16 + g;
    uint32_t ob[64];
    float acc[128];
    const float CS = 1.4426950408889634f * 0.0625f;
    TM(0);
#pragma unroll 1
    for (int hh = 0; hh < 2; ++hh) {
      gemm_k448_n256<ACL>(r, acc, wg, lane);
      TM(1);
      if (hh == 1) {
        if ((tid & 127) == 0) asm volatile("cp.async.bulk.wait_group.read 0;" ::: "memory");
        bar_sync(1 + wg, 128);
      }
      store_tile_bf16<false>(sb + SM_Q, acc, rloc, t4);
      fence_async_smem();
      bar_sync(1 + wg, 128);
      float m0 = -INFINITY, m1 = -INFINITY, l0 = 0.f, l1 = 0.f;
      const uint32_t qa0 = sb + SM_Q + wg * 8192;
      if (wg == 1) bar_arrive(3, 256);
      TM(2);
      bar_sync(3 + wg, 256);
#pragma unroll 1
      for (int t = 0; t < 4; ++t) {
        float s[64];
        TM(3);
        {
          uint32_t qa = qa0; asm volatile("" : "+r"(qa));
          uint32_t ka = r.wait(); uint32_t rel0 = r.empty(); r.next();
          wg_fence();
#pragma unroll
          for (int k = 0; k < 8; ++k)
            wgmma_m64n128k16_ss(s, mk_desc(qa + (k >> 2) * 16384 + (k & 3) * 32, 16, 1024),
                                mk_desc(ka + (k >> 2) * 16384 + (k & 3) * 32, 16, 1024), k != 0);
          wg_commit();
          uint32_t kb = r.wait(); uint32_t rel1 = r.empty(); r.next();
          wg_fence();
#pragma unroll
          for (int k = 0; k < 8; ++k)
            wgmma_m64n128k16_ss(s, mk_desc(qa + (2 + (k >> 2)) * 16384 + (k & 3) * 32, 16, 1024),
                                mk_desc(kb + (k >> 2) * 16384 + (k & 3) * 32, 16, 1024), 1);
          wg_commit();
          bar_arrive(4 - wg, 256);
          wg_wait<1>(); ring_release<ACL>(rel0, lane);
          wg_wait<0>(); ring_release<ACL>(rel1, lane);
        }
        TM(4);
        float mx0 = m0, mx1 = m1;
#pragma unroll
        for (int j = 0; j < 16; ++j) {
          uint32_t a = pack_bf16(s[4 * j], s[4 * j + 1]), b = pack_bf16(s[4 * j + 2], s[4 * j + 3]);
          s[4 * j] = bf_lo(a); s[4 * j + 1] = bf_hi(a); s[4 * j + 2] = bf_lo(b); s[4 * j + 3] = bf_hi(b);
          mx0 = fmaxf(mx0, fmaxf(s[4 * j], s[4 * j + 1])); mx1 = fmaxf(mx1, fmaxf(s[4 * j + 2], s[4 * j + 3]));
        }
        mx0 = fmaxf(mx0, __shfl_xor_sync(0xffffffffu, mx0, 1)); mx0 = fmaxf(mx0, __shfl_xor_sync(0xffffffffu, mx0, 2));
        mx1 = fmaxf(mx1, __shfl_xor_sync(0xffffffffu, mx1, 1)); mx1 = fmaxf(mx1, __shfl_xor_sync(0xffffffffu, mx1, 2));
        const float c0 = ex2((m0 - mx0) * CS), c1 = ex2((m1 - mx1) * CS);
        m0 = mx0; m1 = mx1;
        const float nb0 = -mx0 * CS, nb1 = -mx1 * CS;
        float ps0 = 0.f, ps1 = 0.f;
        uint32_t pa[32];
#pragma unroll
        for (int j = 0; j < 16; ++j) {
          float e0 = ex2(fmaf(s[4 * j], CS, nb0)), e1 = ex2(fmaf(s[4 * j + 1], CS, nb0));
          float e2 = ex2(fmaf(s[4 * j + 2], CS, nb1)), e3 = ex2(fmaf(s[4 * j + 3], CS, nb1));
          ps0 += e0 + e1; ps1 += e2 + e3;
          pa[2 * j] = pack_bf16(e0, e1); pa[2 * j + 1] = pack_bf16(e2, e3);
        }
        l0 = l0 * c0 + ps0; l1 = l1 * c1 + ps1;
        if (t > 0) {
#pragma unroll
          for (int j = 0; j < 32; ++j) { acc[4 * j] *= c0; acc[4 * j + 1] *= c0; acc[4 * j + 2] *= c1; acc[4 * j + 3] *= c1; }
        }
#pragma unroll
        for (int j = 0; j < 32; ++j) asm volatile("" : "+r"(pa[j]));
#pragma unroll
        for (int j = 0; j < 128; ++j) asm volatile("" : "+f"(acc[j]));
        asm volatile("" : "+f"(l0), "+f"(l1));
        TM(5);
        bar_sync(3 + wg, 256);
        TM(6);
        {
          uint32_t va = r.wait(); uint32_t rel0 = r.empty(); r.next();
          wg_fence();
#pragma unroll
          for (int k = 0; k < 4; ++k)
            wgmma_m64n256k16_rs_tb(acc, pa[4 * k], pa[4 * k + 1], pa[4 * k + 2], pa[4 * k + 3],
                                   mk_desc(va + k * 2048, 8192, 1024), (t | k) != 0);
          wg_commit();
          uint32_t vb = r.wait(); uint32_t rel1 = r.empty(); r.next();
          wg_fence();
#pragma unroll
          for (int k = 0; k < 4; ++k)
            wgmma_m64n256k16_rs_tb(acc, pa[16 + 4 * k], pa[16 + 4 * k + 1], pa[16 + 4 * k + 2], pa[16 + 4 * k + 3],
                                   mk_desc(vb + k * 2048, 8192, 1024), 1);
          wg_commit();
          if (t == 3 && wg == 0) bar_arrive(4, 256);
          wg_wait<1>(); ring_release<ACL>(rel0, lane);
          wg_wait<0>(); ring_release<ACL>(rel1, lane);
        }
      }
      TM(7);
      l0 += __shfl_xor_sync(0xffffffffu, l0, 1); l0 += __shfl_xor_sync(0xffffffffu, l0, 2);
      l1 += __shfl_xor_sync(0xffffffffu, l1, 1); l1 += __shfl_xor_sync(0xffffffffu, l1, 2);
      const float i0 = 1.f / l0, i1 = 1.f / l1;
#pragma unroll
      for (int j = 0; j < 32; ++j) {
        ob[2 * j] = pack_bf16(acc[4 * j] * i0, acc[4 * j + 1] * i0);
        ob[2 * j + 1] = pack_bf16(acc[4 * j + 2] * i1, acc[4 * j + 3] * i1);
      }
      if (hh == 0) {
        uint32_t row0 = sb + SM_Q + rloc * 128, row1 = row0 + 8 * 128;
        uint32_t sw = (uint32_t)(rloc & 7);
#pragma unroll
        for (int j = 0; j < 32; ++j) {
          uint32_t off = (uint32_t)(j >> 3) * 16384 + ((((uint32_t)j & 7) ^ sw) << 4) + t4 * 4;
          asm volatile("st.shared.b32 [%0], %1;" ::"r"(row0 + off), "r"(ob[2 * j]) : "memory");
          asm volatile("st.shared.b32 [%0], %1;" ::"r"(row1 + off), "r"(ob[2 * j + 1]) : "memory");
        }
        fence_async_smem();
        bar_sync(1 + wg, 128);
        if ((tid & 127) == 0) {
          for (int c = 0; c < 4; ++c)
            asm volatile("cp.async.bulk.tensor.2d.global.shared::cta.bulk_group [%0, {%2, %3}], [%1];"
                         ::"l"(&tm_oAs), "r"(sb + SM_Q + c * 16384 + wg * 8192), "r"(c * 64), "r"(kvh * SEQ + qt * 128 + wg * 64) : "memory");
          asm volatile("cp.async.bulk.commit_group;" ::: "memory");
        }
      }
    }
    if ((tid & 127) == 0) asm volatile("cp.async.bulk.wait_group 0;" ::: "memory");
    mbar_arrive(bar_oA);
    mbar_wait(bar_oAf, 0);
    TM(8);
    r.shrink();
    out_proj<4, 4, ACL>(r, ob, sb + SM_Q + wg * 8192, &tm_acc, qt * 128 + wg * 64 + warp * 16,
                   sb + SM_RING + (NS - 1) * STG + (wg * 4 + warp) * 4096, lane);
    TM(9);
  }
  cluster_sync_all();
  GT_MAX(5);
}

constexpr uint32_t F_STG = 57344, F_A = 0, F_RING = 57344, F_BAR = F_RING + 3 * F_STG, F_TOTAL = F_BAR + 256 + 1024;

template <int WG>
__device__ __forceinline__ void ffn_gemm(Ring& r, float (&acc)[128], uint32_t abase, int lane) {
  uint32_t prel = 0;
#pragma unroll
  for (int c = 0; c < 7; ++c) {
    uint32_t wb = r.wait(); uint32_t wrel = r.empty(); r.next();
    uint64_t da = mk_desc(abase + c * 8192, 16, 1024);
    uint64_t db = mk_desc(wb + WG * 32768, 8192, 1024);
    wg_fence();
#pragma unroll
    for (int k = 0; k < 4; ++k) {
      if (WG == 0) wgmma_m64n256k16_ss_tb(acc, da + k * 2, db + k * 128, (c | k) != 0);
      else wgmma_m64n192k16_ss_tb(acc, da + k * 2, db + k * 128, (c | k) != 0);
    }
    wg_commit();
    if (c > 0) { wg_wait<1>(); ring_release<2>(prel, lane); }
    prel = wrel;
  }
  wg_wait<0>();
  ring_release<2>(prel, lane);
}

template <int WG>
__device__ __forceinline__ void ffn_consumer(Ring& r, uint32_t sb, uint32_t bar_a, int rt, int warp, int lane, const CUtensorMap* tm) {
  const int g = lane >> 2, t4 = lane & 3, row = warp * 16 + g;
  float acc[128];
  TM(20);
  mbar_wait(bar_a, 0);
  TM(21);
  ffn_gemm<WG>(r, acc, sb + F_A, lane);
  TM(22);
  bar_sync(5, 256);
  {
    uint32_t row0 = sb + F_A + WG * 32768 + row * 128, row1 = row0 + 8 * 128;
    uint32_t sw = (uint32_t)(row & 7);
#pragma unroll
    for (int j = 0; j < (WG == 0 ? 32 : 24); ++j) {
      uint32_t off = (uint32_t)(j >> 3) * 8192 + ((((uint32_t)j & 7) ^ sw) << 4) + t4 * 4;
      asm volatile("st.shared.b32 [%0], %1;" ::"r"(row0 + off), "r"(pack_bf16(fmaxf(acc[4 * j], 0.f), fmaxf(acc[4 * j + 1], 0.f))) : "memory");
      asm volatile("st.shared.b32 [%0], %1;" ::"r"(row1 + off), "r"(pack_bf16(fmaxf(acc[4 * j + 2], 0.f), fmaxf(acc[4 * j + 3], 0.f))) : "memory");
    }
  }
  fence_async_smem();
  bar_sync(5, 256);
  TM(23);
  ffn_gemm<WG>(r, acc, sb + F_A, lane);
  TM(24);
  bar_sync(5, 256);
  const int r0 = rt * 64 + warp * 16, c0 = WG * 256;
  const uint32_t stg = sb + (WG * 4 + warp) * 16384;
  red_rows<16, 0, 128, false>(stg, tm, r0, c0, acc, 0, lane);
  red_rows<16, 0, 128, false>(stg + 4096, tm, r0 + 8, c0, acc, 2, lane);
  if (WG == 0) {
    red_rows<16, 64, 128, false>(stg + 8192, tm, r0, c0 + 128, acc, 0, lane);
    red_rows<16, 64, 128, false>(stg + 12288, tm, r0 + 8, c0 + 128, acc, 2, lane);
  } else {
    red_rows<8, 64, 128, false>(stg + 8192, tm, r0, c0 + 128, acc, 0, lane);
    red_rows<8, 64, 128, false>(stg + 12288, tm, r0 + 8, c0 + 128, acc, 2, lane);
  }
  if (lane == 0) asm volatile("cp.async.bulk.wait_group 0;" ::: "memory");
  TM(25);
}

__global__ void __cluster_dims__(2, 1, 1) __launch_bounds__(384, 1)
ffn_kernel(const __grid_constant__ CUtensorMap tm_h2, const __grid_constant__ CUtensorMap tm_w1,
           const __grid_constant__ CUtensorMap tm_w2, const __grid_constant__ CUtensorMap tm_acc) {
  extern __shared__ uint8_t smem_raw[];
  const uint32_t sb = (smem_u32(smem_raw) + 1023) & ~1023u;
  const int tid = threadIdx.x, wg = tid >> 7, lane = tid & 31;
  const int rt = blockIdx.x, sl = blockIdx.y;
  const uint32_t rank = cluster_rank();
  Ring r; r.base = sb + F_RING; r.full0 = sb + F_BAR; r.empty0 = sb + F_BAR + 64; r.st = 0; r.ph = 0; r.nst = 3; r.stg = F_STG;
  const uint32_t bar_a = sb + F_BAR + 128;
  if (tid == 0) {
    for (int i = 0; i < 3; ++i) { mbar_init(r.full0 + 8 * i, 1); mbar_init(r.empty0 + 8 * i, 16); }
    mbar_init(bar_a, 1);
    asm volatile("fence.mbarrier_init.release.cluster;" ::: "memory");
  }
  cluster_sync_all();
  if (wg == 2) {
    asm volatile("setmaxnreg.dec.sync.aligned.u32 24;");
    if (tid == 256) {
      const int b0 = rank ? 4 : 0, b1 = rank ? 7 : 4;
      pdl_wait();
      mbar_expect_tx(bar_a, 57344);
      for (int k = 0; k < 7; ++k) tma_load(sb + F_A + k * 8192, &tm_h2, k * 64, rt * 64, bar_a);
      for (int c = 0; c < 14; ++c) {
        uint32_t b = r.acquire(F_STG);
        for (int bx = b0; bx < b1; ++bx) {
          if (c < 7) tma_load_mc(b + bx * 8192, &tm_w1, sl * 448 + bx * 64, c * 64, r.full(), 3);
          else tma_load_mc(b + bx * 8192, &tm_w2, bx * 64, sl * 448 + (c - 7) * 64, r.full(), 3);
        }
        r.next();
      }
    }
  } else {
    asm volatile("setmaxnreg.inc.sync.aligned.u32 240;");
    pdl_wait();
    GT_MIN(8);
    const int warp = (tid >> 5) & 3;
    if (wg == 0) ffn_consumer<0>(r, sb, bar_a, rt, warp, lane, &tm_acc);
    else ffn_consumer<1>(r, sb, bar_a, rt, warp, lane, &tm_acc);
  }
  cluster_sync_all();
  GT_MAX(9);
}

__device__ __forceinline__ void l2_prefetch(const void* p, uint32_t bytes) {
  asm volatile("cp.async.bulk.prefetch.L2.global [%0], %1;" ::"l"(p), "r"(bytes) : "memory");
}
__global__ void __launch_bounds__(512) mod_kernel(const __nv_bfloat16* __restrict__ c, const __nv_bfloat16* __restrict__ wm,
                                                  const uint8_t* __restrict__ wq, const uint8_t* __restrict__ kc,
                                                  const uint8_t* __restrict__ vc, const uint8_t* __restrict__ wo,
                                                  const uint8_t* __restrict__ w1, const uint8_t* __restrict__ w2) {
  __shared__ float red[32][33];
  const int tid = threadIdx.x;
  pdl_launch();
  GT_MIN(0);
  if (blockIdx.x < 84) {
    const int cl = tid & 15, kg = tid >> 4;
    const int col = blockIdx.x * 32 + cl * 2;
    uint32_t v[14];
#pragma unroll
    for (int i = 0; i < 14; ++i) v[i] = *reinterpret_cast<const uint32_t*>(wm + (size_t)(kg * 14 + i) * (6 * DM) + col);
    float a0 = 0.f, a1 = 0.f;
#pragma unroll
    for (int i = 0; i < 14; ++i) {
      float cv = __bfloat162float(c[kg * 14 + i]);
      float sv = rbf(cv / (1.f + __expf(-cv)));
      a0 = fmaf(sv, bf_lo(v[i]), a0); a1 = fmaf(sv, bf_hi(v[i]), a1);
    }
    red[kg][cl * 2] = a0; red[kg][cl * 2 + 1] = a1;
    __syncthreads();
    if (tid < 32) {
      float s = 0.f;
#pragma unroll
      for (int i = 0; i < 32; ++i) s += red[i][tid];
      g_mod[blockIdx.x * 32 + tid] = rbf(s);
    }
  } else {
    {
      const int i = (1 << 30);
      constexpr int NQ = 896, NKV = 512, NF = 392;
      if (i < NQ) l2_prefetch(wq + (size_t)i * 4096, 4096);
      else if (i < NQ + NKV) { int j = i - NQ; l2_prefetch(kc + ((size_t)(j >> 6) * SKV + (SKV - WIN)) * 512 + (size_t)(j & 63) * 4096, 4096); }
      else if (i < NQ + 2 * NKV) { int j = i - NQ - NKV; l2_prefetch(vc + ((size_t)(j >> 6) * SKV + (SKV - WIN)) * 512 + (size_t)(j & 63) * 4096, 4096); }
      else if (i < 2 * NQ + 2 * NKV) l2_prefetch(wo + (size_t)(i - NQ - 2 * NKV) * 4096, 4096);
      else if (i < 2 * NQ + 2 * NKV + NF) l2_prefetch(w1 + (size_t)(i - 2 * NQ - 2 * NKV) * 4096, 4096);
      else if (i < 2 * NQ + 2 * NKV + 2 * NF) l2_prefetch(w2 + (size_t)(i - 2 * NQ - 2 * NKV - NF) * 4096, 4096);
    }
    float4 z = make_float4(0.f, 0.f, 0.f, 0.f);
    const int n4 = SEQ * DM / 4;
    for (int i = (blockIdx.x - 84) * 512 + tid; i < n4; i += (gridDim.x - 84) * 512) {
      reinterpret_cast<float4*>(g_acc1)[i] = z; reinterpret_cast<float4*>(g_acc2)[i] = z;
    }
  }
  if (blockIdx.x < 84) GT_MAX(1); else GT_MAX(13);
}

__device__ __forceinline__ void ln_row(const float (&x)[14], const float* __restrict__ shift, const float* __restrict__ scale,
                                       __nv_bfloat16* __restrict__ out, int lane) {
  float2 sc[7], sh[7];
#pragma unroll
  for (int i = 0; i < 7; ++i) {
    sc[i] = *reinterpret_cast<const float2*>(scale + i * 64 + lane * 2);
    sh[i] = *reinterpret_cast<const float2*>(shift + i * 64 + lane * 2);
  }
  float s = 0.f;
#pragma unroll
  for (int i = 0; i < 14; ++i) s += x[i];
#pragma unroll
  for (int o = 16; o; o >>= 1) s += __shfl_xor_sync(0xffffffffu, s, o);
  const float mean = s * (1.f / DM);
  float q = 0.f;
#pragma unroll
  for (int i = 0; i < 14; ++i) { float d = x[i] - mean; q = fmaf(d, d, q); }
#pragma unroll
  for (int o = 16; o; o >>= 1) q += __shfl_xor_sync(0xffffffffu, q, o);
  const float mb = rbf(mean), vb = rbf(q * (1.f / DM));
  const float den = rbf(sqrtf(rbf(vb + 1e-5f)));
#pragma unroll
  for (int i = 0; i < 7; ++i) {
    int col = i * 64 + lane * 2;
    float y0 = rbf(rbf(x[2 * i] - mb) / den), y1 = rbf(rbf(x[2 * i + 1] - mb) / den);
    y0 = rbf(y0 * rbf(1.f + sc[i].x)); y1 = rbf(y1 * rbf(1.f + sc[i].y));
    *reinterpret_cast<uint32_t*>(out + col) = pack_bf16(y0 + sh[i].x, y1 + sh[i].y);
  }
}

__global__ void __launch_bounds__(256) ln1_kernel(const __nv_bfloat16* __restrict__ x) {
  const int lane = threadIdx.x & 31, row = blockIdx.x * 8 + (threadIdx.x >> 5);
  float v[14];
#pragma unroll
  for (int i = 0; i < 7; ++i) {
    uint32_t u = *reinterpret_cast<const uint32_t*>(x + (size_t)row * DM + i * 64 + lane * 2);
    v[2 * i] = bf_lo(u); v[2 * i + 1] = bf_hi(u);
  }
  pdl_wait();
  GT_MIN(2);
  ln_row(v, g_mod + 0 * DM, g_mod + 1 * DM, g_h + (size_t)row * DM, lane);
  GT_MAX(3);
  pdl_launch();
}

__global__ void __launch_bounds__(256) ln2_kernel(const __nv_bfloat16* __restrict__ x) {
  const int lane = threadIdx.x & 31, row = blockIdx.x * 8 + (threadIdx.x >> 5);
  float v[14];
  uint32_t xu[7];
#pragma unroll
  for (int i = 0; i < 7; ++i) xu[i] = *reinterpret_cast<const uint32_t*>(x + (size_t)row * DM + i * 64 + lane * 2);
  pdl_wait();
  GT_MIN(6);
  float2 av[7], gv[7];
#pragma unroll
  for (int i = 0; i < 7; ++i) {
    av[i] = *reinterpret_cast<const float2*>(g_acc1 + (size_t)row * DM + i * 64 + lane * 2);
    gv[i] = *reinterpret_cast<const float2*>(g_mod + 2 * DM + i * 64 + lane * 2);
  }
#pragma unroll
  for (int i = 0; i < 7; ++i) {
    int col = i * 64 + lane * 2;
    uint32_t u = xu[i];
    float t0 = rbf(gv[i].x * rbf(av[i].x)), t1 = rbf(gv[i].y * rbf(av[i].y));
    v[2 * i] = rbf(bf_lo(u) + t0); v[2 * i + 1] = rbf(bf_hi(u) + t1);
    *reinterpret_cast<uint32_t*>(g_x1 + (size_t)row * DM + col) = pack_bf16(v[2 * i], v[2 * i + 1]);
  }
  ln_row(v, g_mod + 3 * DM, g_mod + 4 * DM, g_h2 + (size_t)row * DM, lane);
  GT_MAX(7);
  pdl_launch();
}

__global__ void __launch_bounds__(256) final_kernel(__nv_bfloat16* __restrict__ out) {
  pdl_wait();
  GT_MIN(10);
  const int i = blockIdx.x * 256 + threadIdx.x;
  const int col = (i * 2) % DM;
  uint32_t u = reinterpret_cast<const uint32_t*>(g_x1)[i];
  float2 a = reinterpret_cast<const float2*>(g_acc2)[i];
  float t0 = rbf(g_mod[5 * DM + col] * rbf(a.x)), t1 = rbf(g_mod[5 * DM + col + 1] * rbf(a.y));
  reinterpret_cast<uint32_t*>(out)[i] = pack_bf16(bf_lo(u) + t0, bf_hi(u) + t1);
  GT_MAX(11);
}

typedef CUresult (*EncodeFn)(CUtensorMap*, CUtensorMapDataType, cuuint32_t, void*, const cuuint64_t*, const cuuint64_t*,
                             const cuuint32_t*, const cuuint32_t*, CUtensorMapInterleave, CUtensorMapSwizzle,
                             CUtensorMapL2promotion, CUtensorMapFloatOOBfill);

static CUtensorMap make_map(EncodeFn enc, const void* ptr, uint64_t cols, uint64_t rows, uint32_t bx, uint32_t by,
                            bool f32 = false) {
  CUtensorMap m;
  cuuint64_t dims[2] = {cols, rows};
  cuuint64_t strides[1] = {cols * (f32 ? 4 : 2)};
  cuuint32_t box[2] = {bx, by};
  cuuint32_t es[2] = {1, 1};
  enc(&m, f32 ? CU_TENSOR_MAP_DATA_TYPE_FLOAT32 : CU_TENSOR_MAP_DATA_TYPE_BFLOAT16, 2, const_cast<void*>(ptr), dims, strides, box, es, CU_TENSOR_MAP_INTERLEAVE_NONE,
      CU_TENSOR_MAP_SWIZZLE_128B, CU_TENSOR_MAP_L2_PROMOTION_L2_256B, CU_TENSOR_MAP_FLOAT_OOB_FILL_NONE);
  return m;
}

template <typename... Args>
static void launch(void (*k)(Args...), dim3 grid, dim3 block, size_t smem, bool pdl, Args... args) {
  cudaLaunchConfig_t cfg = {};
  cfg.gridDim = grid; cfg.blockDim = block; cfg.dynamicSmemBytes = smem; cfg.stream = cudaStreamPerThread;
  cudaLaunchAttribute at[1];
  at[0].id = cudaLaunchAttributeProgrammaticStreamSerialization; at[0].val.programmaticStreamSerializationAllowed = 1;
  cfg.attrs = at; cfg.numAttrs = pdl ? 1 : 0;
  cudaLaunchKernelEx(&cfg, k, args...);
}

extern "C" void kernel_launch(void* const* d_in, const int* in_sizes, int n_in, void* d_out, int out_size) {
  const __nv_bfloat16* x = (const __nv_bfloat16*)d_in[0];
  const void* kc = d_in[1]; const void* vc = d_in[2]; const void* wq = d_in[3]; const void* wo = d_in[4];
  const void* w1 = d_in[6]; const void* w2 = d_in[7];
  const __nv_bfloat16* c = (const __nv_bfloat16*)d_in[8];
  const __nv_bfloat16* wm = (const __nv_bfloat16*)d_in[9];

  void* fn = nullptr; cudaDriverEntryPointQueryResult qr;
  cudaGetDriverEntryPoint("cuTensorMapEncodeTiled", &fn, cudaEnableDefault, &qr);
  EncodeFn enc = (EncodeFn)fn;
  void *p_h, *p_oA, *p_h2, *p_a1, *p_a2;
  cudaGetSymbolAddress(&p_a1, g_acc1); cudaGetSymbolAddress(&p_a2, g_acc2);
  cudaGetSymbolAddress(&p_h, g_h); cudaGetSymbolAddress(&p_oA, g_oA); cudaGetSymbolAddress(&p_h2, g_h2);
  CUtensorMap tm_h = make_map(enc, p_h, DM, SEQ, 64, 128);
  CUtensorMap tm_wq = make_map(enc, wq, 4096, DM, 64, 64);
  CUtensorMap tm_k = make_map(enc, kc, DH, HKV * SKV, 64, 128);
  CUtensorMap tm_v = make_map(enc, vc, DH, HKV * SKV, 64, 64);
  CUtensorMap tm_wo = make_map(enc, wo, DM, 4096, 64, 64);
  CUtensorMap tm_oA = make_map(enc, p_oA, DH, HKV * SEQ, 64, 128);
  CUtensorMap tm_oAs = make_map(enc, p_oA, DH, HKV * SEQ, 64, 64);
  CUtensorMap tm_a1 = make_map(enc, p_a1, DM, SEQ, 32, 8, true), tm_a2 = make_map(enc, p_a2, DM, SEQ, 32, 8, true);
  CUtensorMap tm_h2 = make_map(enc, p_h2, DM, SEQ, 64, 64);
  CUtensorMap tm_w1 = make_map(enc, w1, DFF, DM, 64, 64);
  CUtensorMap tm_w2 = make_map(enc, w2, DM, DFF, 64, 64);
  cudaFuncSetAttribute(attn_kernel, cudaFuncAttributeMaxDynamicSharedMemorySize, SM_TOTAL);
  cudaFuncSetAttribute(ffn_kernel, cudaFuncAttributeMaxDynamicSharedMemorySize, F_TOTAL);

  launch(mod_kernel, dim3(84 + 90), dim3(512), 0, false, c, wm, (const uint8_t*)wq, (const uint8_t*)kc, (const uint8_t*)vc,
         (const uint8_t*)wo, (const uint8_t*)w1, (const uint8_t*)w2);
  launch(ln1_kernel, dim3(SEQ / 8), dim3(256), 0, true, x);
  launch(attn_kernel, dim3(16, 8), dim3(384), SM_TOTAL, true, tm_h, tm_wq, tm_k, tm_v, tm_wo, tm_oA, tm_oAs, tm_a1);
  launch(ln2_kernel, dim3(SEQ / 8), dim3(256), 0, true, x);
  launch(ffn_kernel, dim3(32, 4), dim3(384), F_TOTAL, true, tm_h2, tm_w1, tm_w2, tm_a2);
  launch(final_kernel, dim3(SEQ * DM / 512), dim3(256), 0, true, (__nv_bfloat16*)d_out);
}
```

```cpp
#include <cuda_runtime.h>
#include <cuda_bf16.h>
#include <cuda.h>
#include <stdint.h>

constexpr int SEQ = 2048, DM = 448, HKV = 8, SKV = 2048, DH = 256, WIN = 512, DFF = 1792;

__device__ __align__(1024) float          g_mod[6 * DM];
__device__ __align__(1024) __nv_bfloat16  g_h[SEQ * DM];
__device__ __align__(1024) __nv_bfloat16  g_oA[HKV * SEQ * DH];
__device__ __align__(1024) float          g_acc1[SEQ * DM];
__device__ __align__(1024) float          g_acc2[SEQ * DM];
__device__ __align__(1024) __nv_bfloat16  g_x1[SEQ * DM];
__device__ __align__(1024) __nv_bfloat16  g_h2[SEQ * DM];
__device__ unsigned int g_cnt[32];

__device__ __forceinline__ uint32_t smem_u32(const void* p) { return (uint32_t)__cvta_generic_to_shared(p); }
__device__ __forceinline__ void mbar_init(uint32_t bar, uint32_t cnt) {
  asm volatile("mbarrier.init.shared::cta.b64 [%0], %1;" ::"r"(bar), "r"(cnt));
}
__device__ __forceinline__ void mbar_expect_tx(uint32_t bar, uint32_t bytes) {
  asm volatile("mbarrier.arrive.expect_tx.shared::cta.b64 _, [%0], %1;" ::"r"(bar), "r"(bytes) : "memory");
}
__device__ __forceinline__ void mbar_arrive(uint32_t bar) {
  asm volatile("mbarrier.arrive.shared::cta.b64 _, [%0];" ::"r"(bar) : "memory");
}
__device__ __forceinline__ void mbar_arrive_remote(uint32_t bar, uint32_t cta) {
  asm volatile("{\n.reg .b32 ra;\nmapa.shared::cluster.u32 ra, %0, %1;\n"
               "mbarrier.arrive.shared::cluster.b64 _, [ra];\n}\n" ::"r"(bar), "r"(cta) : "memory");
}
__device__ __forceinline__ void mbar_wait(uint32_t bar, uint32_t parity) {
  asm volatile("{\n.reg .pred p;\nLAB_WAIT:\n"
               "mbarrier.try_wait.parity.shared::cta.b64 p, [%0], %1, 0x989680;\n"
               "@p bra LAB_DONE;\nbra LAB_WAIT;\nLAB_DONE:\n}\n" ::"r"(bar), "r"(parity) : "memory");
}
__device__ __forceinline__ void mbar_wait_cluster(uint32_t bar, uint32_t parity) {
  asm volatile("{\n.reg .pred p;\nLAB_WAIT:\n"
               "mbarrier.try_wait.parity.acquire.cluster.shared::cta.b64 p, [%0], %1, 0x989680;\n"
               "@p bra LAB_DONE;\nbra LAB_WAIT;\nLAB_DONE:\n}\n" ::"r"(bar), "r"(parity) : "memory");
}
__device__ __forceinline__ void tma_load(uint32_t dst, const CUtensorMap* m, int c0, int c1, uint32_t bar) {
  asm volatile("cp.async.bulk.tensor.2d.shared::cluster.global.mbarrier::complete_tx::bytes [%0], [%1, {%3, %4}], [%2];"
               ::"r"(dst), "l"(m), "r"(bar), "r"(c0), "r"(c1) : "memory");
}
__device__ __forceinline__ void tma_load_mc(uint32_t dst, const CUtensorMap* m, int c0, int c1, uint32_t bar, uint16_t mask) {
  asm volatile("cp.async.bulk.tensor.2d.shared::cluster.global.mbarrier::complete_tx::bytes.multicast::cluster [%0], [%1, {%3, %4}], [%2], %5;"
               ::"r"(dst), "l"(m), "r"(bar), "r"(c0), "r"(c1), "h"(mask) : "memory");
}
__device__ __forceinline__ void cluster_sync_all() {
  asm volatile("barrier.cluster.arrive.release.aligned;\nbarrier.cluster.wait.acquire.aligned;\n" ::: "memory");
}
__device__ __forceinline__ uint32_t cluster_rank() { uint32_t r; asm volatile("mov.u32 %0, %%cluster_ctarank;" : "=r"(r)); return r; }
__device__ __forceinline__ void wg_fence() { asm volatile("wgmma.fence.sync.aligned;" ::: "memory"); }
__device__ __forceinline__ void wg_commit() { asm volatile("wgmma.commit_group.sync.aligned;" ::: "memory"); }
template <int N> __device__ __forceinline__ void wg_wait() { asm volatile("wgmma.wait_group.sync.aligned %0;" ::"n"(N) : "memory"); }
__device__ __forceinline__ void bar_sync(int id, int n) { asm volatile("bar.sync %0, %1;" ::"r"(id), "r"(n) : "memory"); }
__device__ __forceinline__ void bar_arrive(int id, int n) { asm volatile("bar.arrive %0, %1;" ::"r"(id), "r"(n) : "memory"); }
__device__ __forceinline__ void fence_async_smem() { asm volatile("fence.proxy.async.shared::cta;" ::: "memory"); }
__device__ __forceinline__ void fence_async() { asm volatile("fence.proxy.async;" ::: "memory"); }
__device__ __forceinline__ uint64_t mk_desc(uint32_t saddr, uint32_t lbo, uint32_t sbo) {
  return (uint64_t)((saddr & 0x3FFFF) >> 4) | ((uint64_t)(lbo >> 4) << 16) | ((uint64_t)(sbo >> 4) << 32) | (1ull << 62);
}
__device__ __forceinline__ uint32_t pack_bf16(float lo, float hi) {
  uint32_t r; asm("cvt.rn.bf16x2.f32 %0, %1, %2;" : "=r"(r) : "f"(hi), "f"(lo)); return r;
}
__device__ __forceinline__ float bf_lo(uint32_t v) { return __uint_as_float(v << 16); }
__device__ __forceinline__ float bf_hi(uint32_t v) { return __uint_as_float(v & 0xFFFF0000u); }
__device__ __forceinline__ float rbf(float x) { return __bfloat162float(__float2bfloat16_rn(x)); }
__device__ __forceinline__ float ex2(float x) { float r; asm("ex2.approx.ftz.f32 %0, %1;" : "=f"(r) : "f"(x)); return r; }
__device__ __forceinline__ void red_add_v2(float* p, float a, float b) {
  asm volatile("red.global.add.v2.f32 [%0], {%1, %2};" ::"l"(p), "f"(a), "f"(b) : "memory");
}
__device__ __forceinline__ void pdl_wait() { asm volatile("griddepcontrol.wait;" ::: "memory"); }
__device__ __forceinline__ void pdl_launch() { asm volatile("griddepcontrol.launch_dependents;" ::: "memory"); }

__device__ __forceinline__ void wgmma_m64n256k16_ss_tb(float (&d)[128], uint64_t da, uint64_t db, int sc) {
  asm volatile("{\n.reg .pred p;\nsetp.ne.b32 p, %130, 0;\n"
    "wgmma.mma_async.sync.aligned.m64n256k16.f32.bf16.bf16 {%0, %1, %2, %3, %4, %5, %6, %7, %8, %9, %10, %11, %12, %13, %14, %15, %16, %17, %18, %19, %20, %21, %22, %23, %24, %25, %26, %27, %28, %29, %30, %31, %32, %33, %34, %35, %36, %37, %38, %39, %40, %41, %42, %43, %44, %45, %46, %47, %48, %49, %50, %51, %52, %53, %54, %55, %56, %57, %58, %59, %60, %61, %62, %63, %64, %65, %66, %67, %68, %69, %70, %71, %72, %73, %74, %75, %76, %77, %78, %79, %80, %81, %82, %83, %84, %85, %86, %87, %88, %89, %90, %91, %92, %93, %94, %95, %96, %97, %98, %99, %100, %101, %102, %103, %104, %105, %106, %107, %108, %109, %110, %111, %112, %113, %114, %115, %116, %117, %118, %119, %120, %121, %122, %123, %124, %125, %126, %127}, %128, %129, p, 1, 1, 0, 1;\n}\n"
    : "+f"(d[0]), "+f"(d[1]), "+f"(d[2]), "+f"(d[3]), "+f"(d[4]), "+f"(d[5]), "+f"(d[6]), "+f"(d[7]), "+f"(d[8]), "+f"(d[9]), "+f"(d[10]), "+f"(d[11]), "+f"(d[12]), "+f"(d[13]), "+f"(d[14]), "+f"(d[15]), "+f"(d[16]), "+f"(d[17]), "+f"(d[18]), "+f"(d[19]), "+f"(d[20]), "+f"(d[21]), "+f"(d[22]), "+f"(d[23]), "+f"(d[24]), "+f"(d[25]), "+f"(d[26]), "+f"(d[27]), "+f"(d[28]), "+f"(d[29]), "+f"(d[30]), "+f"(d[31]), "+f"(d[32]), "+f"(d[33]), "+f"(d[34]), "+f"(d[35]), "+f"(d[36]), "+f"(d[37]), "+f"(d[38]), "+f"(d[39]), "+f"(d[40]), "+f"(d[41]), "+f"(d[42]), "+f"(d[43]), "+f"(d[44]), "+f"(d[45]), "+f"(d[46]), "+f"(d[47]), "+f"(d[48]), "+f"(d[49]), "+f"(d[50]), "+f"(d[51]), "+f"(d[52]), "+f"(d[53]), "+f"(d[54]), "+f"(d[55]), "+f"(d[56]), "+f"(d[57]), "+f"(d[58]), "+f"(d[59]), "+f"(d[60]), "+f"(d[61]), "+f"(d[62]), "+f"(d[63]), "+f"(d[64]), "+f"(d[65]), "+f"(d[66]), "+f"(d[67]), "+f"(d[68]), "+f"(d[69]), "+f"(d[70]), "+f"(d[71]), "+f"(d[72]), "+f"(d[73]), "+f"(d[74]), "+f"(d[75]), "+f"(d[76]), "+f"(d[77]), "+f"(d[78]), "+f"(d[79]), "+f"(d[80]), "+f"(d[81]), "+f"(d[82]), "+f"(d[83]), "+f"(d[84]), "+f"(d[85]), "+f"(d[86]), "+f"(d[87]), "+f"(d[88]), "+f"(d[89]), "+f"(d[90]), "+f"(d[91]), "+f"(d[92]), "+f"(d[93]), "+f"(d[94]), "+f"(d[95]), "+f"(d[96]), "+f"(d[97]), "+f"(d[98]), "+f"(d[99]), "+f"(d[100]), "+f"(d[101]), "+f"(d[102]), "+f"(d[103]), "+f"(d[104]), "+f"(d[105]), "+f"(d[106]), "+f"(d[107]), "+f"(d[108]), "+f"(d[109]), "+f"(d[110]), "+f"(d[111]), "+f"(d[112]), "+f"(d[113]), "+f"(d[114]), "+f"(d[115]), "+f"(d[116]), "+f"(d[117]), "+f"(d[118]), "+f"(d[119]), "+f"(d[120]), "+f"(d[121]), "+f"(d[122]), "+f"(d[123]), "+f"(d[124]), "+f"(d[125]), "+f"(d[126]), "+f"(d[127])
    : "l"(da), "l"(db), "r"(sc));
}
__device__ __forceinline__ void wgmma_m64n128k16_ss(float (&d)[64], uint64_t da, uint64_t db, int sc) {
  asm volatile("{\n.reg .pred p;\nsetp.ne.b32 p, %66, 0;\n"
    "wgmma.mma_async.sync.aligned.m64n128k16.f32.bf16.bf16 {%0, %1, %2, %3, %4, %5, %6, %7, %8, %9, %10, %11, %12, %13, %14, %15, %16, %17, %18, %19, %20, %21, %22, %23, %24, %25, %26, %27, %28, %29, %30, %31, %32, %33, %34, %35, %36, %37, %38, %39, %40, %41, %42, %43, %44, %45, %46, %47, %48, %49, %50, %51, %52, %53, %54, %55, %56, %57, %58, %59, %60, %61, %62, %63}, %64, %65, p, 1, 1, 0, 0;\n}\n"
    : "+f"(d[0]), "+f"(d[1]), "+f"(d[2]), "+f"(d[3]), "+f"(d[4]), "+f"(d[5]), "+f"(d[6]), "+f"(d[7]), "+f"(d[8]), "+f"(d[9]), "+f"(d[10]), "+f"(d[11]), "+f"(d[12]), "+f"(d[13]), "+f"(d[14]), "+f"(d[15]), "+f"(d[16]), "+f"(d[17]), "+f"(d[18]), "+f"(d[19]), "+f"(d[20]), "+f"(d[21]), "+f"(d[22]), "+f"(d[23]), "+f"(d[24]), "+f"(d[25]), "+f"(d[26]), "+f"(d[27]), "+f"(d[28]), "+f"(d[29]), "+f"(d[30]), "+f"(d[31]), "+f"(d[32]), "+f"(d[33]), "+f"(d[34]), "+f"(d[35]), "+f"(d[36]), "+f"(d[37]), "+f"(d[38]), "+f"(d[39]), "+f"(d[40]), "+f"(d[41]), "+f"(d[42]), "+f"(d[43]), "+f"(d[44]), "+f"(d[45]), "+f"(d[46]), "+f"(d[47]), "+f"(d[48]), "+f"(d[49]), "+f"(d[50]), "+f"(d[51]), "+f"(d[52]), "+f"(d[53]), "+f"(d[54]), "+f"(d[55]), "+f"(d[56]), "+f"(d[57]), "+f"(d[58]), "+f"(d[59]), "+f"(d[60]), "+f"(d[61]), "+f"(d[62]), "+f"(d[63])
    : "l"(da), "l"(db), "r"(sc));
}
__device__ __forceinline__ void wgmma_m64n256k16_rs_tb(float (&d)[128], uint32_t a0, uint32_t a1, uint32_t a2, uint32_t a3, uint64_t db, int sc) {
  asm volatile("{\n.reg .pred p;\nsetp.ne.b32 p, %133, 0;\n"
    "wgmma.mma_async.sync.aligned.m64n256k16.f32.bf16.bf16 {%0, %1, %2, %3, %4, %5, %6, %7, %8, %9, %10, %11, %12, %13, %14, %15, %16, %17, %18, %19, %20, %21, %22, %23, %24, %25, %26, %27, %28, %29, %30, %31, %32, %33, %34, %35, %36, %37, %38, %39, %40, %41, %42, %43, %44, %45, %46, %47, %48, %49, %50, %51, %52, %53, %54, %55, %56, %57, %58, %59, %60, %61, %62, %63, %64, %65, %66, %67, %68, %69, %70, %71, %72, %73, %74, %75, %76, %77, %78, %79, %80, %81, %82, %83, %84, %85, %86, %87, %88, %89, %90, %91, %92, %93, %94, %95, %96, %97, %98, %99, %100, %101, %102, %103, %104, %105, %106, %107, %108, %109, %110, %111, %112, %113, %114, %115, %116, %117, %118, %119, %120, %121, %122, %123, %124, %125, %126, %127}, {%128, %129, %130, %131}, %132, p, 1, 1, 1;\n}\n"
    : "+f"(d[0]), "+f"(d[1]), "+f"(d[2]), "+f"(d[3]), "+f"(d[4]), "+f"(d[5]), "+f"(d[6]), "+f"(d[7]), "+f"(d[8]), "+f"(d[9]), "+f"(d[10]), "+f"(d[11]), "+f"(d[12]), "+f"(d[13]), "+f"(d[14]), "+f"(d[15]), "+f"(d[16]), "+f"(d[17]), "+f"(d[18]), "+f"(d[19]), "+f"(d[20]), "+f"(d[21]), "+f"(d[22]), "+f"(d[23]), "+f"(d[24]), "+f"(d[25]), "+f"(d[26]), "+f"(d[27]), "+f"(d[28]), "+f"(d[29]), "+f"(d[30]), "+f"(d[31]), "+f"(d[32]), "+f"(d[33]), "+f"(d[34]), "+f"(d[35]), "+f"(d[36]), "+f"(d[37]), "+f"(d[38]), "+f"(d[39]), "+f"(d[40]), "+f"(d[41]), "+f"(d[42]), "+f"(d[43]), "+f"(d[44]), "+f"(d[45]), "+f"(d[46]), "+f"(d[47]), "+f"(d[48]), "+f"(d[49]), "+f"(d[50]), "+f"(d[51]), "+f"(d[52]), "+f"(d[53]), "+f"(d[54]), "+f"(d[55]), "+f"(d[56]), "+f"(d[57]), "+f"(d[58]), "+f"(d[59]), "+f"(d[60]), "+f"(d[61]), "+f"(d[62]), "+f"(d[63]), "+f"(d[64]), "+f"(d[65]), "+f"(d[66]), "+f"(d[67]), "+f"(d[68]), "+f"(d[69]), "+f"(d[70]), "+f"(d[71]), "+f"(d[72]), "+f"(d[73]), "+f"(d[74]), "+f"(d[75]), "+f"(d[76]), "+f"(d[77]), "+f"(d[78]), "+f"(d[79]), "+f"(d[80]), "+f"(d[81]), "+f"(d[82]), "+f"(d[83]), "+f"(d[84]), "+f"(d[85]), "+f"(d[86]), "+f"(d[87]), "+f"(d[88]), "+f"(d[89]), "+f"(d[90]), "+f"(d[91]), "+f"(d[92]), "+f"(d[93]), "+f"(d[94]), "+f"(d[95]), "+f"(d[96]), "+f"(d[97]), "+f"(d[98]), "+f"(d[99]), "+f"(d[100]), "+f"(d[101]), "+f"(d[102]), "+f"(d[103]), "+f"(d[104]), "+f"(d[105]), "+f"(d[106]), "+f"(d[107]), "+f"(d[108]), "+f"(d[109]), "+f"(d[110]), "+f"(d[111]), "+f"(d[112]), "+f"(d[113]), "+f"(d[114]), "+f"(d[115]), "+f"(d[116]), "+f"(d[117]), "+f"(d[118]), "+f"(d[119]), "+f"(d[120]), "+f"(d[121]), "+f"(d[122]), "+f"(d[123]), "+f"(d[124]), "+f"(d[125]), "+f"(d[126]), "+f"(d[127])
    : "r"(a0), "r"(a1), "r"(a2), "r"(a3), "l"(db), "r"(sc));
}
__device__ __forceinline__ void wgmma_m64n128k16_ss_tb(float (&d)[64], uint64_t da, uint64_t db, int sc) {
  asm volatile("{\n.reg .pred p;\nsetp.ne.b32 p, %66, 0;\n"
    "wgmma.mma_async.sync.aligned.m64n128k16.f32.bf16.bf16 {%0, %1, %2, %3, %4, %5, %6, %7, %8, %9, %10, %11, %12, %13, %14, %15, %16, %17, %18, %19, %20, %21, %22, %23, %24, %25, %26, %27, %28, %29, %30, %31, %32, %33, %34, %35, %36, %37, %38, %39, %40, %41, %42, %43, %44, %45, %46, %47, %48, %49, %50, %51, %52, %53, %54, %55, %56, %57, %58, %59, %60, %61, %62, %63}, %64, %65, p, 1, 1, 0, 1;\n}\n"
    : "+f"(d[0]), "+f"(d[1]), "+f"(d[2]), "+f"(d[3]), "+f"(d[4]), "+f"(d[5]), "+f"(d[6]), "+f"(d[7]), "+f"(d[8]), "+f"(d[9]), "+f"(d[10]), "+f"(d[11]), "+f"(d[12]), "+f"(d[13]), "+f"(d[14]), "+f"(d[15]), "+f"(d[16]), "+f"(d[17]), "+f"(d[18]), "+f"(d[19]), "+f"(d[20]), "+f"(d[21]), "+f"(d[22]), "+f"(d[23]), "+f"(d[24]), "+f"(d[25]), "+f"(d[26]), "+f"(d[27]), "+f"(d[28]), "+f"(d[29]), "+f"(d[30]), "+f"(d[31]), "+f"(d[32]), "+f"(d[33]), "+f"(d[34]), "+f"(d[35]), "+f"(d[36]), "+f"(d[37]), "+f"(d[38]), "+f"(d[39]), "+f"(d[40]), "+f"(d[41]), "+f"(d[42]), "+f"(d[43]), "+f"(d[44]), "+f"(d[45]), "+f"(d[46]), "+f"(d[47]), "+f"(d[48]), "+f"(d[49]), "+f"(d[50]), "+f"(d[51]), "+f"(d[52]), "+f"(d[53]), "+f"(d[54]), "+f"(d[55]), "+f"(d[56]), "+f"(d[57]), "+f"(d[58]), "+f"(d[59]), "+f"(d[60]), "+f"(d[61]), "+f"(d[62]), "+f"(d[63])
    : "l"(da), "l"(db), "r"(sc));
}
__device__ __forceinline__ void wgmma_m64n128k16_rs_tb(float (&d)[64], uint32_t a0, uint32_t a1, uint32_t a2, uint32_t a3, uint64_t db, int sc) {
  asm volatile("{\n.reg .pred p;\nsetp.ne.b32 p, %69, 0;\n"
    "wgmma.mma_async.sync.aligned.m64n128k16.f32.bf16.bf16 {%0, %1, %2, %3, %4, %5, %6, %7, %8, %9, %10, %11, %12, %13, %14, %15, %16, %17, %18, %19, %20, %21, %22, %23, %24, %25, %26, %27, %28, %29, %30, %31, %32, %33, %34, %35, %36, %37, %38, %39, %40, %41, %42, %43, %44, %45, %46, %47, %48, %49, %50, %51, %52, %53, %54, %55, %56, %57, %58, %59, %60, %61, %62, %63}, {%64, %65, %66, %67}, %68, p, 1, 1, 1;\n}\n"
    : "+f"(d[0]), "+f"(d[1]), "+f"(d[2]), "+f"(d[3]), "+f"(d[4]), "+f"(d[5]), "+f"(d[6]), "+f"(d[7]), "+f"(d[8]), "+f"(d[9]), "+f"(d[10]), "+f"(d[11]), "+f"(d[12]), "+f"(d[13]), "+f"(d[14]), "+f"(d[15]), "+f"(d[16]), "+f"(d[17]), "+f"(d[18]), "+f"(d[19]), "+f"(d[20]), "+f"(d[21]), "+f"(d[22]), "+f"(d[23]), "+f"(d[24]), "+f"(d[25]), "+f"(d[26]), "+f"(d[27]), "+f"(d[28]), "+f"(d[29]), "+f"(d[30]), "+f"(d[31]), "+f"(d[32]), "+f"(d[33]), "+f"(d[34]), "+f"(d[35]), "+f"(d[36]), "+f"(d[37]), "+f"(d[38]), "+f"(d[39]), "+f"(d[40]), "+f"(d[41]), "+f"(d[42]), "+f"(d[43]), "+f"(d[44]), "+f"(d[45]), "+f"(d[46]), "+f"(d[47]), "+f"(d[48]), "+f"(d[49]), "+f"(d[50]), "+f"(d[51]), "+f"(d[52]), "+f"(d[53]), "+f"(d[54]), "+f"(d[55]), "+f"(d[56]), "+f"(d[57]), "+f"(d[58]), "+f"(d[59]), "+f"(d[60]), "+f"(d[61]), "+f"(d[62]), "+f"(d[63])
    : "r"(a0), "r"(a1), "r"(a2), "r"(a3), "l"(db), "r"(sc));
}
__device__ __forceinline__ void wgmma_m64n64k16_ss_tb(float (&d)[32], uint64_t da, uint64_t db, int sc) {
  asm volatile("{\n.reg .pred p;\nsetp.ne.b32 p, %34, 0;\n"
    "wgmma.mma_async.sync.aligned.m64n64k16.f32.bf16.bf16 {%0, %1, %2, %3, %4, %5, %6, %7, %8, %9, %10, %11, %12, %13, %14, %15, %16, %17, %18, %19, %20, %21, %22, %23, %24, %25, %26, %27, %28, %29, %30, %31}, %32, %33, p, 1, 1, 0, 1;\n}\n"
    : "+f"(d[0]), "+f"(d[1]), "+f"(d[2]), "+f"(d[3]), "+f"(d[4]), "+f"(d[5]), "+f"(d[6]), "+f"(d[7]), "+f"(d[8]), "+f"(d[9]), "+f"(d[10]), "+f"(d[11]), "+f"(d[12]), "+f"(d[13]), "+f"(d[14]), "+f"(d[15]), "+f"(d[16]), "+f"(d[17]), "+f"(d[18]), "+f"(d[19]), "+f"(d[20]), "+f"(d[21]), "+f"(d[22]), "+f"(d[23]), "+f"(d[24]), "+f"(d[25]), "+f"(d[26]), "+f"(d[27]), "+f"(d[28]), "+f"(d[29]), "+f"(d[30]), "+f"(d[31])
    : "l"(da), "l"(db), "r"(sc));
}
__device__ __forceinline__ void wgmma_m64n64k16_rs_tb(float (&d)[32], uint32_t a0, uint32_t a1, uint32_t a2, uint32_t a3, uint64_t db, int sc) {
  asm volatile("{\n.reg .pred p;\nsetp.ne.b32 p, %37, 0;\n"
    "wgmma.mma_async.sync.aligned.m64n64k16.f32.bf16.bf16 {%0, %1, %2, %3, %4, %5, %6, %7, %8, %9, %10, %11, %12, %13, %14, %15, %16, %17, %18, %19, %20, %21, %22, %23, %24, %25, %26, %27, %28, %29, %30, %31}, {%32, %33, %34, %35}, %36, p, 1, 1, 1;\n}\n"
    : "+f"(d[0]), "+f"(d[1]), "+f"(d[2]), "+f"(d[3]), "+f"(d[4]), "+f"(d[5]), "+f"(d[6]), "+f"(d[7]), "+f"(d[8]), "+f"(d[9]), "+f"(d[10]), "+f"(d[11]), "+f"(d[12]), "+f"(d[13]), "+f"(d[14]), "+f"(d[15]), "+f"(d[16]), "+f"(d[17]), "+f"(d[18]), "+f"(d[19]), "+f"(d[20]), "+f"(d[21]), "+f"(d[22]), "+f"(d[23]), "+f"(d[24]), "+f"(d[25]), "+f"(d[26]), "+f"(d[27]), "+f"(d[28]), "+f"(d[29]), "+f"(d[30]), "+f"(d[31])
    : "r"(a0), "r"(a1), "r"(a2), "r"(a3), "l"(db), "r"(sc));
}
__device__ __forceinline__ void wgmma_m64n192k16_ss_tb(float (&d)[128], uint64_t da, uint64_t db, int sc) {
  asm volatile("{\n.reg .pred p;\nsetp.ne.b32 p, %98, 0;\n"
    "wgmma.mma_async.sync.aligned.m64n192k16.f32.bf16.bf16 {%0, %1, %2, %3, %4, %5, %6, %7, %8, %9, %10, %11, %12, %13, %14, %15, %16, %17, %18, %19, %20, %21, %22, %23, %24, %25, %26, %27, %28, %29, %30, %31, %32, %33, %34, %35, %36, %37, %38, %39, %40, %41, %42, %43, %44, %45, %46, %47, %48, %49, %50, %51, %52, %53, %54, %55, %56, %57, %58, %59, %60, %61, %62, %63, %64, %65, %66, %67, %68, %69, %70, %71, %72, %73, %74, %75, %76, %77, %78, %79, %80, %81, %82, %83, %84, %85, %86, %87, %88, %89, %90, %91, %92, %93, %94, %95}, %96, %97, p, 1, 1, 0, 1;\n}\n"
    : "+f"(d[0]), "+f"(d[1]), "+f"(d[2]), "+f"(d[3]), "+f"(d[4]), "+f"(d[5]), "+f"(d[6]), "+f"(d[7]), "+f"(d[8]), "+f"(d[9]), "+f"(d[10]), "+f"(d[11]), "+f"(d[12]), "+f"(d[13]), "+f"(d[14]), "+f"(d[15]), "+f"(d[16]), "+f"(d[17]), "+f"(d[18]), "+f"(d[19]), "+f"(d[20]), "+f"(d[21]), "+f"(d[22]), "+f"(d[23]), "+f"(d[24]), "+f"(d[25]), "+f"(d[26]), "+f"(d[27]), "+f"(d[28]), "+f"(d[29]), "+f"(d[30]), "+f"(d[31]), "+f"(d[32]), "+f"(d[33]), "+f"(d[34]), "+f"(d[35]), "+f"(d[36]), "+f"(d[37]), "+f"(d[38]), "+f"(d[39]), "+f"(d[40]), "+f"(d[41]), "+f"(d[42]), "+f"(d[43]), "+f"(d[44]), "+f"(d[45]), "+f"(d[46]), "+f"(d[47]), "+f"(d[48]), "+f"(d[49]), "+f"(d[50]), "+f"(d[51]), "+f"(d[52]), "+f"(d[53]), "+f"(d[54]), "+f"(d[55]), "+f"(d[56]), "+f"(d[57]), "+f"(d[58]), "+f"(d[59]), "+f"(d[60]), "+f"(d[61]), "+f"(d[62]), "+f"(d[63]), "+f"(d[64]), "+f"(d[65]), "+f"(d[66]), "+f"(d[67]), "+f"(d[68]), "+f"(d[69]), "+f"(d[70]), "+f"(d[71]), "+f"(d[72]), "+f"(d[73]), "+f"(d[74]), "+f"(d[75]), "+f"(d[76]), "+f"(d[77]), "+f"(d[78]), "+f"(d[79]), "+f"(d[80]), "+f"(d[81]), "+f"(d[82]), "+f"(d[83]), "+f"(d[84]), "+f"(d[85]), "+f"(d[86]), "+f"(d[87]), "+f"(d[88]), "+f"(d[89]), "+f"(d[90]), "+f"(d[91]), "+f"(d[92]), "+f"(d[93]), "+f"(d[94]), "+f"(d[95])
    : "l"(da), "l"(db), "r"(sc));
}

#define TM(id)
#define GT_MIN(i)
#define GT_MAX(i)

constexpr int NS = 5;
constexpr uint32_t STG = 32768;
constexpr uint32_t SM_Q = 0;
constexpr uint32_t SM_RING = 65536;
constexpr uint32_t SM_BAR = SM_RING + NS * STG;
constexpr uint32_t SM_TOTAL = SM_BAR + 256 + 1024;

struct Ring {
  uint32_t base, full0, empty0, st, ph, nst, stg;
  __device__ __forceinline__ void init(uint32_t sb) { base = sb + SM_RING; full0 = sb + SM_BAR; empty0 = sb + SM_BAR + 64; st = 0; ph = 0; nst = NS; stg = STG; }
  __device__ __forceinline__ uint32_t phase() const { return (ph >> st) & 1; }
  __device__ __forceinline__ uint32_t buf() const { return base + st * stg; }
  __device__ __forceinline__ uint32_t full() const { return full0 + st * 8; }
  __device__ __forceinline__ uint32_t empty() const { return empty0 + st * 8; }
  __device__ __forceinline__ void next() { ph ^= 1u << st; st = (st + 1 >= nst) ? 0 : st + 1; }
  __device__ __forceinline__ void shrink() { nst = NS - 1; if (st >= nst) st = 0; }
  __device__ __forceinline__ uint32_t acquire(uint32_t bytes) {
    mbar_wait(empty(), phase() ^ 1); mbar_expect_tx(full(), bytes); return buf();
  }
  __device__ __forceinline__ uint32_t wait() { mbar_wait(full(), phase()); return buf(); }
};
template <int CL = 2>
__device__ __forceinline__ void ring_release(uint32_t empty_bar, int lane) {
  __syncwarp();
  if (lane < CL) mbar_arrive_remote(empty_bar, (uint32_t)lane);
}

template <int CL>
__device__ __forceinline__ void gemm_k448_n256(Ring& r, float (&acc)[128], int wg, int lane) {
  uint32_t hb = 0, hrel = 0, prel = 0, phrel = 0;
#pragma unroll
  for (int c = 0; c < 7; ++c) {
    if ((c & 1) == 0) { hb = r.wait(); hrel = r.empty(); r.next(); }
    uint32_t wb = r.wait(); uint32_t wrel = r.empty(); r.next();
    uint64_t da = mk_desc(hb + (c & 1) * 16384 + wg * 8192, 16, 1024);
    uint64_t db = mk_desc(wb, 8192, 1024);
    wg_fence();
#pragma unroll
    for (int k = 0; k < 4; ++k) wgmma_m64n256k16_ss_tb(acc, da + k * 2, db + k * 128, (c | k) != 0);
    wg_commit();
    if (c > 0) {
      wg_wait<1>();
      ring_release<CL>(prel, lane);
      if ((c & 1) == 0) ring_release<CL>(phrel, lane);
    }
    prel = wrel; phrel = hrel;
  }
  wg_wait<0>();
  ring_release<CL>(prel, lane); ring_release<CL>(phrel, lane);
}

template <bool RELU>
__device__ __forceinline__ void store_tile_bf16(uint32_t base, const float (&acc)[128], int rloc, int t4) {
  uint32_t row0 = base + rloc * 128, row1 = row0 + 8 * 128;
  uint32_t sw = (uint32_t)(rloc & 7);
#pragma unroll
  for (int j = 0; j < 32; ++j) {
    uint32_t off = (uint32_t)(j >> 3) * 16384 + ((((uint32_t)j & 7) ^ sw) << 4) + t4 * 4;
    float a = acc[4 * j], b = acc[4 * j + 1], c = acc[4 * j + 2], d = acc[4 * j + 3];
    if (RELU) { a = fmaxf(a, 0.f); b = fmaxf(b, 0.f); c = fmaxf(c, 0.f); d = fmaxf(d, 0.f); }
    asm volatile("st.shared.b32 [%0], %1;" ::"r"(row0 + off), "r"(pack_bf16(a, b)) : "memory");
    asm volatile("st.shared.b32 [%0], %1;" ::"r"(row1 + off), "r"(pack_bf16(c, d)) : "memory");
  }
}

template <int NJ, int OFF = 0, int SZ = 64, bool WAIT = true>
__device__ __forceinline__ void red_rows(uint32_t stg, const CUtensorMap* tm, int row0, int col0, const float (&a)[SZ], int sel, int lane) {
  asm volatile("" : "+r"(stg), "+r"(lane));
  if (WAIT) {
    if (lane == 0) asm volatile("cp.async.bulk.wait_group.read 0;" ::: "memory");
    __syncwarp();
  }
  const uint32_t g = lane >> 2, t4 = lane & 3;
  const uint32_t wbase = stg + g * 128 + (t4 & 1) * 8;
#pragma unroll
  for (int j = 0; j < NJ; ++j)
    asm volatile("st.shared.v2.f32 [%0], {%1, %2};" ::"r"(wbase + (j >> 2) * 1024 + ((((j & 3) * 2 + (t4 >> 1)) ^ g) << 4)),
                 "f"(a[OFF + 4 * j + sel]), "f"(a[OFF + 4 * j + sel + 1]) : "memory");
  fence_async_smem();
  __syncwarp();
  if (lane == 0) {
#pragma unroll
    for (int b = 0; b < NJ / 4; ++b)
      asm volatile("cp.reduce.async.bulk.tensor.2d.global.shared::cta.add.tile.bulk_group [%0, {%2, %3}], [%1];"
                   ::"l"(tm), "r"(stg + b * 1024), "r"(col0 + b * 32), "r"(row0) : "memory");
    asm volatile("cp.async.bulk.commit_group;" ::: "memory");
  }
}

template <int NSM, int NRG, int CL>
__device__ __forceinline__ void out_proj(Ring& r, const uint32_t (&ob)[64], uint32_t abase,
                                         const CUtensorMap* tm, int roww, uint32_t stg, int lane, uint32_t abar) {
  constexpr int NST = (NSM + NRG) / 2;
  uint32_t prel = 0;
  float accA[64], accB[64];
  float(&cur32)[32] = *reinterpret_cast<float(*)[32]>(&accB[0]);
#pragma unroll
  for (int pass = 0; pass < 4; ++pass) {
    float(&cur)[64] = (pass & 1) ? accB : accA;
    float(&prv)[64] = (pass & 1) ? accA : accB;
#pragma unroll
    for (int st = 0; st < NST; ++st) {
      uint32_t wb = r.wait(); uint32_t rel = r.empty(); r.next();
      if (pass == 0 && 2 * st == NRG && abar) mbar_wait(abar, 0);
      asm volatile("" : "+r"(abase));
      wg_fence();
#pragma unroll
      for (int cc = 0; cc < 2; ++cc) {
        const int c = (2 * st + cc + NSM) % (NSM + NRG);
#pragma unroll
        for (int k = 0; k < 4; ++k) {
          const int sc = (st | cc | k) != 0;
          if (pass < 3) {
            uint64_t db = mk_desc(wb + cc * 16384 + k * 2048, 8192, 1024);
            if (c < NSM) wgmma_m64n128k16_ss_tb(cur, mk_desc(abase + c * 16384 + k * 32, 16, 1024), db, sc);
            else { const int o = (c - NSM) * 16 + 4 * k; wgmma_m64n128k16_rs_tb(cur, ob[o], ob[o + 1], ob[o + 2], ob[o + 3], db, sc); }
          } else {
            uint64_t db = mk_desc(wb + cc * 8192 + k * 2048, 8192, 1024);
            if (c < NSM) wgmma_m64n64k16_ss_tb(cur32, mk_desc(abase + c * 16384 + k * 32, 16, 1024), db, sc);
            else { const int o = (c - NSM) * 16 + 4 * k; wgmma_m64n64k16_rs_tb(cur32, ob[o], ob[o + 1], ob[o + 2], ob[o + 3], db, sc); }
          }
        }
      }
      wg_commit();
      if (pass | st) { wg_wait<1>(); ring_release<CL>(prel, lane); }
      prel = rel;
      if (pass > 0) {
        if (st == 0) red_rows<16>(stg, tm, roww, (pass - 1) * 128, prv, 0, lane);
        if (st == NST / 2) red_rows<16>(stg, tm, roww + 8, (pass - 1) * 128, prv, 2, lane);
      }
    }
  }
  wg_wait<0>(); ring_release<CL>(prel, lane);
  red_rows<8>(stg, tm, roww, 384, accB, 0, lane);
  red_rows<8>(stg, tm, roww + 8, 384, accB, 2, lane);
  if (lane == 0) asm volatile("cp.async.bulk.wait_group 0;" ::: "memory");
}
template <int CL>
__device__ __forceinline__ void out_proj_loads(Ring& r, const CUtensorMap* tm, int krow0, int nch, int rot, uint32_t rank) {
  r.shrink();
  constexpr uint16_t MASK = (1 << CL) - 1;
  for (int pass = 0; pass < 4; ++pass)
    for (int st0 = 0; st0 < nch / 2; ++st0) {
      const int st = (st0 + rot) % (nch / 2);
      if (pass < 3) {
        uint32_t b = r.acquire(32768);
        for (int x = 0; x < 4 / CL; ++x) {
          const int bx = rank * (4 / CL) + x;
          tma_load_mc(b + bx * 8192, tm, pass * 128 + (bx & 1) * 64, krow0 + (2 * st + (bx >> 1)) * 64, r.full(), MASK);
        }
      } else {
        uint32_t b = r.acquire(16384);
        if (CL == 1) { for (int x = 0; x < 2; ++x) tma_load_mc(b + x * 8192, tm, 384, krow0 + (2 * st + x) * 64, r.full(), MASK); }
        else if (rank < 2) tma_load_mc(b + rank * 8192, tm, 384, krow0 + (2 * st + rank) * 64, r.full(), MASK);
      }
      r.next();
    }
}

#define ACL 2
__global__ void __cluster_dims__(ACL, 1, 1) __launch_bounds__(384, 1)
attn_kernel(const __grid_constant__ CUtensorMap tm_h, const __grid_constant__ CUtensorMap tm_wq,
            const __grid_constant__ CUtensorMap tm_k, const __grid_constant__ CUtensorMap tm_v,
            const __grid_constant__ CUtensorMap tm_wo, const __grid_constant__ CUtensorMap tm_oA,
            const __grid_constant__ CUtensorMap tm_oAs, const __grid_constant__ CUtensorMap tm_acc) {
  extern __shared__ uint8_t smem_raw[];
  const uint32_t sb = (smem_u32(smem_raw) + 1023) & ~1023u;
  const int tid = threadIdx.x, wg = tid >> 7, lane = tid & 31;
  const int qt = blockIdx.x, kvh = blockIdx.y;
  const uint32_t rank = cluster_rank();
  Ring r; r.init(sb);
  const uint32_t bar_oA = sb + SM_BAR + 128, bar_oAf = sb + SM_BAR + 136;
  if (tid == 0) {
    for (int i = 0; i < NS; ++i) { mbar_init(r.full0 + 8 * i, 1); mbar_init(r.empty0 + 8 * i, 8 * ACL); }
    mbar_init(bar_oA, 256); mbar_init(bar_oAf, 1);
    asm volatile("fence.mbarrier_init.release.cluster;" ::: "memory");
  }
  cluster_sync_all();
  pdl_wait();
  GT_MIN(4);

  if (wg == 2) {
    asm volatile("setmaxnreg.dec.sync.aligned.u32 24;");
    if (tid == 256) {
      const int krow0 = kvh * SKV + (SKV - WIN);
      for (int hh = 0; hh < 2; ++hh) {
        const int head = kvh * 2 + hh;
        for (int p = 0; p < 4; ++p) {
          int nc = (p < 3) ? 2 : 1;
          uint32_t b = r.acquire(nc * 16384);
          for (int c = 0; c < nc; ++c) tma_load(b + c * 16384, &tm_h, (2 * p + c) * 64, qt * 128, r.full());
          r.next();
          for (int c = 0; c < nc; ++c) {
            b = r.acquire(32768);
            for (int x = 0; x < 4 / ACL; ++x) {
              int bx = rank * 2 + x;
              tma_load_mc(b + bx * 8192, &tm_wq, head * 256 + bx * 64, (2 * p + c) * 64, r.full(), (1 << ACL) - 1);
            }
            r.next();
          }
        }
        for (int t = 0; t < 4; ++t) {
          for (int hf = 0; hf < 2; ++hf) {
            uint32_t b = r.acquire(32768);
            for (int x = 0; x < 2 / ACL; ++x)
              tma_load_mc(b + (rank + x) * 16384, &tm_k, (2 * hf + rank + x) * 64, krow0 + t * 128, r.full(), (1 << ACL) - 1);
            r.next();
          }
          for (int hf = 0; hf < 2; ++hf) {
            uint32_t b = r.acquire(32768);
            for (int x = 0; x < 4 / ACL; ++x) {
              int bx = rank * 2 + x;
              tma_load_mc(b + bx * 8192, &tm_v, bx * 64, krow0 + t * 128 + hf * 64, r.full(), (1 << ACL) - 1);
            }
            r.next();
          }
        }
      }
      mbar_wait(bar_oA, 0);
      mbar_expect_tx(bar_oAf, 65536);
      for (int c = 0; c < 4; ++c) tma_load(sb + SM_Q + c * 16384, &tm_oA, c * 64, kvh * SEQ + qt * 128, bar_oAf);
      out_proj_loads<ACL>(r, &tm_wo, kvh * 512, 8, 2, rank);
    }
  } else {
    asm volatile("setmaxnreg.inc.sync.aligned.u32 240;");
    const int warp = (tid >> 5) & 3, g = lane >> 2, t4 = lane & 3;
    const int rloc = wg * 64 + warp * 16 + g;
    uint32_t ob[64];
    float acc[128];
    const float CS = 1.4426950408889634f * 0.0625f;
    TM(0);
#pragma unroll 1
    for (int hh = 0; hh < 2; ++hh) {
      gemm_k448_n256<ACL>(r, acc, wg, lane);
      TM(1);
      if (hh == 1) {
        if ((tid & 127) == 0) asm volatile("cp.async.bulk.wait_group.read 0;" ::: "memory");
        bar_sync(1 + wg, 128);
      }
      store_tile_bf16<false>(sb + SM_Q, acc, rloc, t4);
      fence_async_smem();
      bar_sync(1 + wg, 128);
      float m0 = -INFINITY, m1 = -INFINITY, l0 = 0.f, l1 = 0.f;
      const uint32_t qa0 = sb + SM_Q + wg * 8192;
      if (wg == 1) bar_arrive(3, 256);
      TM(2);
      bar_sync(3 + wg, 256);
#pragma unroll 1
      for (int t = 0; t < 4; ++t) {
        float s[64];
        TM(3);
        {
          uint32_t qa = qa0; asm volatile("" : "+r"(qa));
          uint32_t ka = r.wait(); uint32_t rel0 = r.empty(); r.next();
          wg_fence();
#pragma unroll
          for (int k = 0; k < 8; ++k)
            wgmma_m64n128k16_ss(s, mk_desc(qa + (k >> 2) * 16384 + (k & 3) * 32, 16, 1024),
                                mk_desc(ka + (k >> 2) * 16384 + (k & 3) * 32, 16, 1024), k != 0);
          wg_commit();
          uint32_t kb = r.wait(); uint32_t rel1 = r.empty(); r.next();
          wg_fence();
#pragma unroll
          for (int k = 0; k < 8; ++k)
            wgmma_m64n128k16_ss(s, mk_desc(qa + (2 + (k >> 2)) * 16384 + (k & 3) * 32, 16, 1024),
                                mk_desc(kb + (k >> 2) * 16384 + (k & 3) * 32, 16, 1024), 1);
          wg_commit();
          bar_arrive(4 - wg, 256);
          wg_wait<1>(); ring_release<ACL>(rel0, lane);
          wg_wait<0>(); ring_release<ACL>(rel1, lane);
        }
        TM(4);
        float mx0 = m0, mx1 = m1;
#pragma unroll
        for (int j = 0; j < 16; ++j) {
          uint32_t a = pack_bf16(s[4 * j], s[4 * j + 1]), b = pack_bf16(s[4 * j + 2], s[4 * j + 3]);
          s[4 * j] = bf_lo(a); s[4 * j + 1] = bf_hi(a); s[4 * j + 2] = bf_lo(b); s[4 * j + 3] = bf_hi(b);
          mx0 = fmaxf(mx0, fmaxf(s[4 * j], s[4 * j + 1])); mx1 = fmaxf(mx1, fmaxf(s[4 * j + 2], s[4 * j + 3]));
        }
        mx0 = fmaxf(mx0, __shfl_xor_sync(0xffffffffu, mx0, 1)); mx0 = fmaxf(mx0, __shfl_xor_sync(0xffffffffu, mx0, 2));
        mx1 = fmaxf(mx1, __shfl_xor_sync(0xffffffffu, mx1, 1)); mx1 = fmaxf(mx1, __shfl_xor_sync(0xffffffffu, mx1, 2));
        const float c0 = ex2((m0 - mx0) * CS), c1 = ex2((m1 - mx1) * CS);
        m0 = mx0; m1 = mx1;
        const float nb0 = -mx0 * CS, nb1 = -mx1 * CS;
        float ps0 = 0.f, ps1 = 0.f;
        uint32_t pa[32];
#pragma unroll
        for (int j = 0; j < 16; ++j) {
          float e0 = ex2(fmaf(s[4 * j], CS, nb0)), e1 = ex2(fmaf(s[4 * j + 1], CS, nb0));
          float e2 = ex2(fmaf(s[4 * j + 2], CS, nb1)), e3 = ex2(fmaf(s[4 * j + 3], CS, nb1));
          ps0 += e0 + e1; ps1 += e2 + e3;
          pa[2 * j] = pack_bf16(e0, e1); pa[2 * j + 1] = pack_bf16(e2, e3);
        }
        l0 = l0 * c0 + ps0; l1 = l1 * c1 + ps1;
        if (t > 0) {
#pragma unroll
          for (int j = 0; j < 32; ++j) { acc[4 * j] *= c0; acc[4 * j + 1] *= c0; acc[4 * j + 2] *= c1; acc[4 * j + 3] *= c1; }
        }
#pragma unroll
        for (int j = 0; j < 32; ++j) asm volatile("" : "+r"(pa[j]));
#pragma unroll
        for (int j = 0; j < 128; ++j) asm volatile("" : "+f"(acc[j]));
        asm volatile("" : "+f"(l0), "+f"(l1));
        TM(5);
        bar_sync(3 + wg, 256);
        TM(6);
        {
          uint32_t va = r.wait(); uint32_t rel0 = r.empty(); r.next();
          wg_fence();
#pragma unroll
          for (int k = 0; k < 4; ++k)
            wgmma_m64n256k16_rs_tb(acc, pa[4 * k], pa[4 * k + 1], pa[4 * k + 2], pa[4 * k + 3],
                                   mk_desc(va + k * 2048, 8192, 1024), (t | k) != 0);
          wg_commit();
          uint32_t vb = r.wait(); uint32_t rel1 = r.empty(); r.next();
          wg_fence();
#pragma unroll
          for (int k = 0; k < 4; ++k)
            wgmma_m64n256k16_rs_tb(acc, pa[16 + 4 * k], pa[16 + 4 * k + 1], pa[16 + 4 * k + 2], pa[16 + 4 * k + 3],
                                   mk_desc(vb + k * 2048, 8192, 1024), 1);
          wg_commit();
          if (t == 3 && wg == 0) bar_arrive(4, 256);
          wg_wait<1>(); ring_release<ACL>(rel0, lane);
          wg_wait<0>(); ring_release<ACL>(rel1, lane);
        }
      }
      TM(7);
      l0 += __shfl_xor_sync(0xffffffffu, l0, 1); l0 += __shfl_xor_sync(0xffffffffu, l0, 2);
      l1 += __shfl_xor_sync(0xffffffffu, l1, 1); l1 += __shfl_xor_sync(0xffffffffu, l1, 2);
      const float i0 = 1.f / l0, i1 = 1.f / l1;
#pragma unroll
      for (int j = 0; j < 32; ++j) {
        ob[2 * j] = pack_bf16(acc[4 * j] * i0, acc[4 * j + 1] * i0);
        ob[2 * j + 1] = pack_bf16(acc[4 * j + 2] * i1, acc[4 * j + 3] * i1);
      }
      if (hh == 0) {
        uint32_t row0 = sb + SM_Q + rloc * 128, row1 = row0 + 8 * 128;
        uint32_t sw = (uint32_t)(rloc & 7);
#pragma unroll
        for (int j = 0; j < 32; ++j) {
          uint32_t off = (uint32_t)(j >> 3) * 16384 + ((((uint32_t)j & 7) ^ sw) << 4) + t4 * 4;
          asm volatile("st.shared.b32 [%0], %1;" ::"r"(row0 + off), "r"(ob[2 * j]) : "memory");
          asm volatile("st.shared.b32 [%0], %1;" ::"r"(row1 + off), "r"(ob[2 * j + 1]) : "memory");
        }
        fence_async_smem();
        bar_sync(1 + wg, 128);
        if ((tid & 127) == 0) {
          for (int c = 0; c < 4; ++c)
            asm volatile("cp.async.bulk.tensor.2d.global.shared::cta.bulk_group [%0, {%2, %3}], [%1];"
                         ::"l"(&tm_oAs), "r"(sb + SM_Q + c * 16384 + wg * 8192), "r"(c * 64), "r"(kvh * SEQ + qt * 128 + wg * 64) : "memory");
          asm volatile("cp.async.bulk.commit_group;" ::: "memory");
        }
      }
    }
    if ((tid & 127) == 0) asm volatile("cp.async.bulk.wait_group 0;" ::: "memory");
    mbar_arrive(bar_oA);
    bar_sync(5, 256);
    TM(8);
    r.shrink();
    out_proj<4, 4, ACL>(r, ob, sb + SM_Q + wg * 8192, &tm_acc, qt * 128 + wg * 64 + warp * 16,
                   sb + SM_RING + (NS - 1) * STG + (wg * 4 + warp) * 4096, lane, bar_oAf);
    TM(9);
  }
  cluster_sync_all();
  GT_MAX(5);
}

constexpr uint32_t F_STG = 57344, F_A = 0, F_RING = 57344, F_BAR = F_RING + 3 * F_STG, F_TOTAL = F_BAR + 256 + 1024;

template <int WG>
__device__ __forceinline__ void ffn_gemm(Ring& r, float (&acc)[128], uint32_t abase, int lane) {
  uint32_t prel = 0;
#pragma unroll
  for (int c = 0; c < 7; ++c) {
    uint32_t wb = r.wait(); uint32_t wrel = r.empty(); r.next();
    uint64_t da = mk_desc(abase + c * 8192, 16, 1024);
    uint64_t db = mk_desc(wb + WG * 32768, 8192, 1024);
    wg_fence();
#pragma unroll
    for (int k = 0; k < 4; ++k) {
      if (WG == 0) wgmma_m64n256k16_ss_tb(acc, da + k * 2, db + k * 128, (c | k) != 0);
      else wgmma_m64n192k16_ss_tb(acc, da + k * 2, db + k * 128, (c | k) != 0);
    }
    wg_commit();
    if (c > 0) { wg_wait<1>(); ring_release<2>(prel, lane); }
    prel = wrel;
  }
  wg_wait<0>();
  ring_release<2>(prel, lane);
}

template <int WG>
__device__ __forceinline__ void ffn_consumer(Ring& r, uint32_t sb, uint32_t bar_a, int rt, int warp, int lane, const CUtensorMap* tm,
                                             __nv_bfloat16* __restrict__ out) {
  const int g = lane >> 2, t4 = lane & 3, row = warp * 16 + g;
  float acc[128];
  TM(20);
  mbar_wait(bar_a, 0);
  TM(21);
  ffn_gemm<WG>(r, acc, sb + F_A, lane);
  TM(22);
  bar_sync(5, 256);
  {
    uint32_t row0 = sb + F_A + WG * 32768 + row * 128, row1 = row0 + 8 * 128;
    uint32_t sw = (uint32_t)(row & 7);
#pragma unroll
    for (int j = 0; j < (WG == 0 ? 32 : 24); ++j) {
      uint32_t off = (uint32_t)(j >> 3) * 8192 + ((((uint32_t)j & 7) ^ sw) << 4) + t4 * 4;
      asm volatile("st.shared.b32 [%0], %1;" ::"r"(row0 + off), "r"(pack_bf16(fmaxf(acc[4 * j], 0.f), fmaxf(acc[4 * j + 1], 0.f))) : "memory");
      asm volatile("st.shared.b32 [%0], %1;" ::"r"(row1 + off), "r"(pack_bf16(fmaxf(acc[4 * j + 2], 0.f), fmaxf(acc[4 * j + 3], 0.f))) : "memory");
    }
  }
  fence_async_smem();
  bar_sync(5, 256);
  TM(23);
  ffn_gemm<WG>(r, acc, sb + F_A, lane);
  TM(24);
  bar_sync(5, 256);
  const int r0 = rt * 64 + warp * 16, c0 = WG * 256;
  const uint32_t stg = sb + (WG * 4 + warp) * 16384;
  red_rows<16, 0, 128, false>(stg, tm, r0, c0, acc, 0, lane);
  red_rows<16, 0, 128, false>(stg + 4096, tm, r0 + 8, c0, acc, 2, lane);
  if (WG == 0) {
    red_rows<16, 64, 128, false>(stg + 8192, tm, r0, c0 + 128, acc, 0, lane);
    red_rows<16, 64, 128, false>(stg + 12288, tm, r0 + 8, c0 + 128, acc, 2, lane);
  } else {
    red_rows<8, 64, 128, false>(stg + 8192, tm, r0, c0 + 128, acc, 0, lane);
    red_rows<8, 64, 128, false>(stg + 12288, tm, r0 + 8, c0 + 128, acc, 2, lane);
  }
  if (lane == 0) asm volatile("cp.async.bulk.wait_group 0;" ::: "memory");
  TM(25);
  __syncwarp();
  fence_async();
  __threadfence();
  bar_sync(5, 256);
  if (WG == 0 && warp == 0 && lane == 0) {
    unsigned int old = atomicAdd(&g_cnt[rt], 1u);
    asm volatile("st.shared.u32 [%0], %1;" ::"r"(sb + F_BAR + 192), "r"(old) : "memory");
  }
  bar_sync(5, 256);
  unsigned int s_last;
  asm volatile("ld.shared.u32 %0, [%1];" : "=r"(s_last) : "r"(sb + F_BAR + 192) : "memory");
  if (s_last == 3) {
    __threadfence();
    const int t = WG * 128 + warp * 32 + lane;
    const size_t base = (size_t)rt * 64 * DM;
#pragma unroll 4
    for (int i = t; i < 64 * DM / 4; i += 256) {
      const int col = (i * 4) % DM;
      float4 a = __ldcg(reinterpret_cast<const float4*>(g_acc2 + base) + i);
      uint2 u = __ldcg(reinterpret_cast<const uint2*>(g_x1 + base) + i);
      float4 gb = *reinterpret_cast<const float4*>(g_mod + 5 * DM + col);
      uint2 o;
      o.x = pack_bf16(bf_lo(u.x) + rbf(gb.x * rbf(a.x)), bf_hi(u.x) + rbf(gb.y * rbf(a.y)));
      o.y = pack_bf16(bf_lo(u.y) + rbf(gb.z * rbf(a.z)), bf_hi(u.y) + rbf(gb.w * rbf(a.w)));
      reinterpret_cast<uint2*>(out + base)[i] = o;
    }
  }
}

__global__ void __cluster_dims__(2, 1, 1) __launch_bounds__(384, 1)
ffn_kernel(const __grid_constant__ CUtensorMap tm_h2, const __grid_constant__ CUtensorMap tm_w1,
           const __grid_constant__ CUtensorMap tm_w2, const __grid_constant__ CUtensorMap tm_acc,
           __nv_bfloat16* __restrict__ out) {
  extern __shared__ uint8_t smem_raw[];
  const uint32_t sb = (smem_u32(smem_raw) + 1023) & ~1023u;
  const int tid = threadIdx.x, wg = tid >> 7, lane = tid & 31;
  const int rt = blockIdx.x, sl = blockIdx.y;
  const uint32_t rank = cluster_rank();
  Ring r; r.base = sb + F_RING; r.full0 = sb + F_BAR; r.empty0 = sb + F_BAR + 64; r.st = 0; r.ph = 0; r.nst = 3; r.stg = F_STG;
  const uint32_t bar_a = sb + F_BAR + 128;
  if (tid == 0) {
    for (int i = 0; i < 3; ++i) { mbar_init(r.full0 + 8 * i, 1); mbar_init(r.empty0 + 8 * i, 16); }
    mbar_init(bar_a, 1);
    asm volatile("fence.mbarrier_init.release.cluster;" ::: "memory");
  }
  cluster_sync_all();
  if (wg == 2) {
    asm volatile("setmaxnreg.dec.sync.aligned.u32 24;");
    if (tid == 256) {
      const int b0 = rank ? 4 : 0, b1 = rank ? 7 : 4;
      pdl_wait();
      mbar_expect_tx(bar_a, 57344);
      for (int k = 0; k < 7; ++k) tma_load(sb + F_A + k * 8192, &tm_h2, k * 64, rt * 64, bar_a);
      for (int c = 0; c < 14; ++c) {
        uint32_t b = r.acquire(F_STG);
        for (int bx = b0; bx < b1; ++bx) {
          if (c < 7) tma_load_mc(b + bx * 8192, &tm_w1, sl * 448 + bx * 64, c * 64, r.full(), 3);
          else tma_load_mc(b + bx * 8192, &tm_w2, bx * 64, sl * 448 + (c - 7) * 64, r.full(), 3);
        }
        r.next();
      }
    }
  } else {
    asm volatile("setmaxnreg.inc.sync.aligned.u32 240;");
    pdl_wait();
    GT_MIN(8);
    const int warp = (tid >> 5) & 3;
    if (wg == 0) ffn_consumer<0>(r, sb, bar_a, rt, warp, lane, &tm_acc, out);
    else ffn_consumer<1>(r, sb, bar_a, rt, warp, lane, &tm_acc, out);
  }
  cluster_sync_all();
  GT_MAX(9);
}

__device__ __forceinline__ void l2_prefetch(const void* p, uint32_t bytes) {
  asm volatile("cp.async.bulk.prefetch.L2.global [%0], %1;" ::"l"(p), "r"(bytes) : "memory");
}
__global__ void __launch_bounds__(512) mod_kernel(const __nv_bfloat16* __restrict__ c, const __nv_bfloat16* __restrict__ wm,
                                                  const uint8_t* __restrict__ wq, const uint8_t* __restrict__ kc,
                                                  const uint8_t* __restrict__ vc, const uint8_t* __restrict__ wo,
                                                  const uint8_t* __restrict__ w1, const uint8_t* __restrict__ w2) {
  __shared__ float red[32][33];
  const int tid = threadIdx.x;
  pdl_launch();
  GT_MIN(0);
  if (blockIdx.x < 84) {
    const int cl = tid & 15, kg = tid >> 4;
    const int col = blockIdx.x * 32 + cl * 2;
    uint32_t v[14];
#pragma unroll
    for (int i = 0; i < 14; ++i) v[i] = *reinterpret_cast<const uint32_t*>(wm + (size_t)(kg * 14 + i) * (6 * DM) + col);
    float a0 = 0.f, a1 = 0.f;
#pragma unroll
    for (int i = 0; i < 14; ++i) {
      float cv = __bfloat162float(c[kg * 14 + i]);
      float sv = rbf(cv / (1.f + __expf(-cv)));
      a0 = fmaf(sv, bf_lo(v[i]), a0); a1 = fmaf(sv, bf_hi(v[i]), a1);
    }
    red[kg][cl * 2] = a0; red[kg][cl * 2 + 1] = a1;
    __syncthreads();
    if (tid < 32) {
      float s = 0.f;
#pragma unroll
      for (int i = 0; i < 32; ++i) s += red[i][tid];
      g_mod[blockIdx.x * 32 + tid] = rbf(s);
    }
  } else {
    {
      const int i = (1 << 30);
      constexpr int NQ = 896, NKV = 512, NF = 392;
      if (i < NQ) l2_prefetch(wq + (size_t)i * 4096, 4096);
      else if (i < NQ + NKV) { int j = i - NQ; l2_prefetch(kc + ((size_t)(j >> 6) * SKV + (SKV - WIN)) * 512 + (size_t)(j & 63) * 4096, 4096); }
      else if (i < NQ + 2 * NKV) { int j = i - NQ - NKV; l2_prefetch(vc + ((size_t)(j >> 6) * SKV + (SKV - WIN)) * 512 + (size_t)(j & 63) * 4096, 4096); }
      else if (i < 2 * NQ + 2 * NKV) l2_prefetch(wo + (size_t)(i - NQ - 2 * NKV) * 4096, 4096);
      else if (i < 2 * NQ + 2 * NKV + NF) l2_prefetch(w1 + (size_t)(i - 2 * NQ - 2 * NKV) * 4096, 4096);
      else if (i < 2 * NQ + 2 * NKV + 2 * NF) l2_prefetch(w2 + (size_t)(i - 2 * NQ - 2 * NKV - NF) * 4096, 4096);
    }
    if (blockIdx.x == 84 && tid < 32) g_cnt[tid] = 0;
    float4 z = make_float4(0.f, 0.f, 0.f, 0.f);
    const int n4 = SEQ * DM / 4;
    for (int i = (blockIdx.x - 84) * 512 + tid; i < n4; i += (gridDim.x - 84) * 512) {
      reinterpret_cast<float4*>(g_acc1)[i] = z; reinterpret_cast<float4*>(g_acc2)[i] = z;
    }
  }
  if (blockIdx.x < 84) GT_MAX(1); else GT_MAX(13);
}

__device__ __forceinline__ void ln_row(const float (&x)[14], const float* __restrict__ shift, const float* __restrict__ scale,
                                       __nv_bfloat16* __restrict__ out, int lane) {
  float2 sc[7], sh[7];
#pragma unroll
  for (int i = 0; i < 7; ++i) {
    sc[i] = *reinterpret_cast<const float2*>(scale + i * 64 + lane * 2);
    sh[i] = *reinterpret_cast<const float2*>(shift + i * 64 + lane * 2);
  }
  float s = 0.f;
#pragma unroll
  for (int i = 0; i < 14; ++i) s += x[i];
#pragma unroll
  for (int o = 16; o; o >>= 1) s += __shfl_xor_sync(0xffffffffu, s, o);
  const float mean = s * (1.f / DM);
  float q = 0.f;
#pragma unroll
  for (int i = 0; i < 14; ++i) { float d = x[i] - mean; q = fmaf(d, d, q); }
#pragma unroll
  for (int o = 16; o; o >>= 1) q += __shfl_xor_sync(0xffffffffu, q, o);
  const float mb = rbf(mean), vb = rbf(q * (1.f / DM));
  const float den = rbf(sqrtf(rbf(vb + 1e-5f)));
#pragma unroll
  for (int i = 0; i < 7; ++i) {
    int col = i * 64 + lane * 2;
    float y0 = rbf(rbf(x[2 * i] - mb) / den), y1 = rbf(rbf(x[2 * i + 1] - mb) / den);
    y0 = rbf(y0 * rbf(1.f + sc[i].x)); y1 = rbf(y1 * rbf(1.f + sc[i].y));
    *reinterpret_cast<uint32_t*>(out + col) = pack_bf16(y0 + sh[i].x, y1 + sh[i].y);
  }
}

__global__ void __launch_bounds__(256) ln1_kernel(const __nv_bfloat16* __restrict__ x) {
  const int lane = threadIdx.x & 31, row = blockIdx.x * 8 + (threadIdx.x >> 5);
  float v[14];
#pragma unroll
  for (int i = 0; i < 7; ++i) {
    uint32_t u = *reinterpret_cast<const uint32_t*>(x + (size_t)row * DM + i * 64 + lane * 2);
    v[2 * i] = bf_lo(u); v[2 * i + 1] = bf_hi(u);
  }
  pdl_wait();
  GT_MIN(2);
  ln_row(v, g_mod + 0 * DM, g_mod + 1 * DM, g_h + (size_t)row * DM, lane);
  GT_MAX(3);
  pdl_launch();
}

__global__ void __launch_bounds__(256) ln2_kernel(const __nv_bfloat16* __restrict__ x) {
  const int lane = threadIdx.x & 31, row = blockIdx.x * 8 + (threadIdx.x >> 5);
  float v[14];
  uint32_t xu[7];
#pragma unroll
  for (int i = 0; i < 7; ++i) xu[i] = *reinterpret_cast<const uint32_t*>(x + (size_t)row * DM + i * 64 + lane * 2);
  pdl_wait();
  GT_MIN(6);
  float2 av[7], gv[7];
#pragma unroll
  for (int i = 0; i < 7; ++i) {
    av[i] = *reinterpret_cast<const float2*>(g_acc1 + (size_t)row * DM + i * 64 + lane * 2);
    gv[i] = *reinterpret_cast<const float2*>(g_mod + 2 * DM + i * 64 + lane * 2);
  }
#pragma unroll
  for (int i = 0; i < 7; ++i) {
    int col = i * 64 + lane * 2;
    uint32_t u = xu[i];
    float t0 = rbf(gv[i].x * rbf(av[i].x)), t1 = rbf(gv[i].y * rbf(av[i].y));
    v[2 * i] = rbf(bf_lo(u) + t0); v[2 * i + 1] = rbf(bf_hi(u) + t1);
    *reinterpret_cast<uint32_t*>(g_x1 + (size_t)row * DM + col) = pack_bf16(v[2 * i], v[2 * i + 1]);
  }
  ln_row(v, g_mod + 3 * DM, g_mod + 4 * DM, g_h2 + (size_t)row * DM, lane);
  GT_MAX(7);
  pdl_launch();
}

__global__ void __launch_bounds__(256) final_kernel(__nv_bfloat16* __restrict__ out) {
  pdl_wait();
  GT_MIN(10);
  const int i = blockIdx.x * 256 + threadIdx.x;
  const int col = (i * 2) % DM;
  uint32_t u = reinterpret_cast<const uint32_t*>(g_x1)[i];
  float2 a = reinterpret_cast<const float2*>(g_acc2)[i];
  float t0 = rbf(g_mod[5 * DM + col] * rbf(a.x)), t1 = rbf(g_mod[5 * DM + col + 1] * rbf(a.y));
  reinterpret_cast<uint32_t*>(out)[i] = pack_bf16(bf_lo(u) + t0, bf_hi(u) + t1);
  GT_MAX(11);
}

typedef CUresult (*EncodeFn)(CUtensorMap*, CUtensorMapDataType, cuuint32_t, void*, const cuuint64_t*, const cuuint64_t*,
                             const cuuint32_t*, const cuuint32_t*, CUtensorMapInterleave, CUtensorMapSwizzle,
                             CUtensorMapL2promotion, CUtensorMapFloatOOBfill);

static CUtensorMap make_map(EncodeFn enc, const void* ptr, uint64_t cols, uint64_t rows, uint32_t bx, uint32_t by,
                            bool f32 = false) {
  CUtensorMap m;
  cuuint64_t dims[2] = {cols, rows};
  cuuint64_t strides[1] = {cols * (f32 ? 4 : 2)};
  cuuint32_t box[2] = {bx, by};
  cuuint32_t es[2] = {1, 1};
  enc(&m, f32 ? CU_TENSOR_MAP_DATA_TYPE_FLOAT32 : CU_TENSOR_MAP_DATA_TYPE_BFLOAT16, 2, const_cast<void*>(ptr), dims, strides, box, es, CU_TENSOR_MAP_INTERLEAVE_NONE,
      CU_TENSOR_MAP_SWIZZLE_128B, CU_TENSOR_MAP_L2_PROMOTION_L2_256B, CU_TENSOR_MAP_FLOAT_OOB_FILL_NONE);
  return m;
}

template <typename... Args>
static void launch(void (*k)(Args...), dim3 grid, dim3 block, size_t smem, bool pdl, Args... args) {
  cudaLaunchConfig_t cfg = {};
  cfg.gridDim = grid; cfg.blockDim = block; cfg.dynamicSmemBytes = smem; cfg.stream = cudaStreamPerThread;
  cudaLaunchAttribute at[1];
  at[0].id = cudaLaunchAttributeProgrammaticStreamSerialization; at[0].val.programmaticStreamSerializationAllowed = 1;
  cfg.attrs = at; cfg.numAttrs = pdl ? 1 : 0;
  cudaLaunchKernelEx(&cfg, k, args...);
}

extern "C" void kernel_launch(void* const* d_in, const int* in_sizes, int n_in, void* d_out, int out_size) {
  const __nv_bfloat16* x = (const __nv_bfloat16*)d_in[0];
  const void* kc = d_in[1]; const void* vc = d_in[2]; const void* wq = d_in[3]; const void* wo = d_in[4];
  const void* w1 = d_in[6]; const void* w2 = d_in[7];
  const __nv_bfloat16* c = (const __nv_bfloat16*)d_in[8];
  const __nv_bfloat16* wm = (const __nv_bfloat16*)d_in[9];

  void* fn = nullptr; cudaDriverEntryPointQueryResult qr;
  cudaGetDriverEntryPoint("cuTensorMapEncodeTiled", &fn, cudaEnableDefault, &qr);
  EncodeFn enc = (EncodeFn)fn;
  void *p_h, *p_oA, *p_h2, *p_a1, *p_a2;
  cudaGetSymbolAddress(&p_a1, g_acc1); cudaGetSymbolAddress(&p_a2, g_acc2);
  cudaGetSymbolAddress(&p_h, g_h); cudaGetSymbolAddress(&p_oA, g_oA); cudaGetSymbolAddress(&p_h2, g_h2);
  CUtensorMap tm_h = make_map(enc, p_h, DM, SEQ, 64, 128);
  CUtensorMap tm_wq = make_map(enc, wq, 4096, DM, 64, 64);
  CUtensorMap tm_k = make_map(enc, kc, DH, HKV * SKV, 64, 128);
  CUtensorMap tm_v = make_map(enc, vc, DH, HKV * SKV, 64, 64);
  CUtensorMap tm_wo = make_map(enc, wo, DM, 4096, 64, 64);
  CUtensorMap tm_oA = make_map(enc, p_oA, DH, HKV * SEQ, 64, 128);
  CUtensorMap tm_oAs = make_map(enc, p_oA, DH, HKV * SEQ, 64, 64);
  CUtensorMap tm_a1 = make_map(enc, p_a1, DM, SEQ, 32, 8, true), tm_a2 = make_map(enc, p_a2, DM, SEQ, 32, 8, true);
  CUtensorMap tm_h2 = make_map(enc, p_h2, DM, SEQ, 64, 64);
  CUtensorMap tm_w1 = make_map(enc, w1, DFF, DM, 64, 64);
  CUtensorMap tm_w2 = make_map(enc, w2, DM, DFF, 64, 64);
  cudaFuncSetAttribute(attn_kernel, cudaFuncAttributeMaxDynamicSharedMemorySize, SM_TOTAL);
  cudaFuncSetAttribute(ffn_kernel, cudaFuncAttributeMaxDynamicSharedMemorySize, F_TOTAL);

  launch(mod_kernel, dim3(84 + 90), dim3(512), 0, false, c, wm, (const uint8_t*)wq, (const uint8_t*)kc, (const uint8_t*)vc,
         (const uint8_t*)wo, (const uint8_t*)w1, (const uint8_t*)w2);
  launch(ln1_kernel, dim3(SEQ / 8), dim3(256), 0, true, x);
  launch(attn_kernel, dim3(16, 8), dim3(384), SM_TOTAL, true, tm_h, tm_wq, tm_k, tm_v, tm_wo, tm_oA, tm_oAs, tm_a1);
  launch(ln2_kernel, dim3(SEQ / 8), dim3(256), 0, true, x);
  launch(ffn_kernel, dim3(32, 4), dim3(384), F_TOTAL, true, tm_h2, tm_w1, tm_w2, tm_a2, (__nv_bfloat16*)d_out);
}
```

```cpp
#include <cuda_runtime.h>
#include <cuda_bf16.h>
#include <cuda.h>
#include <stdint.h>

constexpr int SEQ = 2048, DM = 448, HKV = 8, SKV = 2048, DH = 256, WIN = 512, DFF = 1792;

__device__ __align__(1024) float          g_mod[6 * DM];
__device__ __align__(1024) __nv_bfloat16  g_h[SEQ * DM];
__device__ __align__(1024) __nv_bfloat16  g_oA[HKV * SEQ * DH];
__device__ __align__(1024) float          g_acc1[SEQ * DM];
__device__ __align__(1024) float          g_acc2[SEQ * DM];
__device__ __align__(1024) __nv_bfloat16  g_x1[SEQ * DM];
__device__ __align__(1024) __nv_bfloat16  g_h2[SEQ * DM];

__device__ __forceinline__ uint32_t smem_u32(const void* p) { return (uint32_t)__cvta_generic_to_shared(p); }
__device__ __forceinline__ void mbar_init(uint32_t bar, uint32_t cnt) {
  asm volatile("mbarrier.init.shared::cta.b64 [%0], %1;" ::"r"(bar), "r"(cnt));
}
__device__ __forceinline__ void mbar_expect_tx(uint32_t bar, uint32_t bytes) {
  asm volatile("mbarrier.arrive.expect_tx.shared::cta.b64 _, [%0], %1;" ::"r"(bar), "r"(bytes) : "memory");
}
__device__ __forceinline__ void mbar_arrive(uint32_t bar) {
  asm volatile("mbarrier.arrive.shared::cta.b64 _, [%0];" ::"r"(bar) : "memory");
}
__device__ __forceinline__ void mbar_arrive_remote(uint32_t bar, uint32_t cta) {
  asm volatile("{\n.reg .b32 ra;\nmapa.shared::cluster.u32 ra, %0, %1;\n"
               "mbarrier.arrive.shared::cluster.b64 _, [ra];\n}\n" ::"r"(bar), "r"(cta) : "memory");
}
__device__ __forceinline__ void mbar_wait(uint32_t bar, uint32_t parity) {
  asm volatile("{\n.reg .pred p;\nLAB_WAIT:\n"
               "mbarrier.try_wait.parity.shared::cta.b64 p, [%0], %1, 0x989680;\n"
               "@p bra LAB_DONE;\nbra LAB_WAIT;\nLAB_DONE:\n}\n" ::"r"(bar), "r"(parity) : "memory");
}
__device__ __forceinline__ void mbar_wait_cluster(uint32_t bar, uint32_t parity) {
  asm volatile("{\n.reg .pred p;\nLAB_WAIT:\n"
               "mbarrier.try_wait.parity.acquire.cluster.shared::cta.b64 p, [%0], %1, 0x989680;\n"
               "@p bra LAB_DONE;\nbra LAB_WAIT;\nLAB_DONE:\n}\n" ::"r"(bar), "r"(parity) : "memory");
}
__device__ __forceinline__ void tma_load(uint32_t dst, const CUtensorMap* m, int c0, int c1, uint32_t bar) {
  asm volatile("cp.async.bulk.tensor.2d.shared::cluster.global.mbarrier::complete_tx::bytes [%0], [%1, {%3, %4}], [%2];"
               ::"r"(dst), "l"(m), "r"(bar), "r"(c0), "r"(c1) : "memory");
}
__device__ __forceinline__ void tma_load_mc(uint32_t dst, const CUtensorMap* m, int c0, int c1, uint32_t bar, uint16_t mask) {
  asm volatile("cp.async.bulk.tensor.2d.shared::cluster.global.mbarrier::complete_tx::bytes.multicast::cluster [%0], [%1, {%3, %4}], [%2], %5;"
               ::"r"(dst), "l"(m), "r"(bar), "r"(c0), "r"(c1), "h"(mask) : "memory");
}
__device__ __forceinline__ void cluster_sync_all() {
  asm volatile("barrier.cluster.arrive.release.aligned;\nbarrier.cluster.wait.acquire.aligned;\n" ::: "memory");
}
__device__ __forceinline__ uint32_t cluster_rank() { uint32_t r; asm volatile("mov.u32 %0, %%cluster_ctarank;" : "=r"(r)); return r; }
__device__ __forceinline__ void wg_fence() { asm volatile("wgmma.fence.sync.aligned;" ::: "memory"); }
__device__ __forceinline__ void wg_commit() { asm volatile("wgmma.commit_group.sync.aligned;" ::: "memory"); }
template <int N> __device__ __forceinline__ void wg_wait() { asm volatile("wgmma.wait_group.sync.aligned %0;" ::"n"(N) : "memory"); }
__device__ __forceinline__ void bar_sync(int id, int n) { asm volatile("bar.sync %0, %1;" ::"r"(id), "r"(n) : "memory"); }
__device__ __forceinline__ void bar_arrive(int id, int n) { asm volatile("bar.arrive %0, %1;" ::"r"(id), "r"(n) : "memory"); }
__device__ __forceinline__ void fence_async_smem() { asm volatile("fence.proxy.async.shared::cta;" ::: "memory"); }
__device__ __forceinline__ void fence_async() { asm volatile("fence.proxy.async;" ::: "memory"); }
__device__ __forceinline__ uint64_t mk_desc(uint32_t saddr, uint32_t lbo, uint32_t sbo) {
  return (uint64_t)((saddr & 0x3FFFF) >> 4) | ((uint64_t)(lbo >> 4) << 16) | ((uint64_t)(sbo >> 4) << 32) | (1ull << 62);
}
__device__ __forceinline__ uint32_t pack_bf16(float lo, float hi) {
  uint32_t r; asm("cvt.rn.bf16x2.f32 %0, %1, %2;" : "=r"(r) : "f"(hi), "f"(lo)); return r;
}
__device__ __forceinline__ float bf_lo(uint32_t v) { return __uint_as_float(v << 16); }
__device__ __forceinline__ float bf_hi(uint32_t v) { return __uint_as_float(v & 0xFFFF0000u); }
__device__ __forceinline__ float rbf(float x) { return __bfloat162float(__float2bfloat16_rn(x)); }
__device__ __forceinline__ float ex2(float x) { float r; asm("ex2.approx.ftz.f32 %0, %1;" : "=f"(r) : "f"(x)); return r; }
__device__ __forceinline__ void red_add_v2(float* p, float a, float b) {
  asm volatile("red.global.add.v2.f32 [%0], {%1, %2};" ::"l"(p), "f"(a), "f"(b) : "memory");
}
__device__ __forceinline__ void pdl_wait() { asm volatile("griddepcontrol.wait;" ::: "memory"); }
__device__ __forceinline__ void pdl_launch() { asm volatile("griddepcontrol.launch_dependents;" ::: "memory"); }

__device__ __forceinline__ void wgmma_m64n256k16_ss_tb(float (&d)[128], uint64_t da, uint64_t db, int sc) {
  asm volatile("{\n.reg .pred p;\nsetp.ne.b32 p, %130, 0;\n"
    "wgmma.mma_async.sync.aligned.m64n256k16.f32.bf16.bf16 {%0, %1, %2, %3, %4, %5, %6, %7, %8, %9, %10, %11, %12, %13, %14, %15, %16, %17, %18, %19, %20, %21, %22, %23, %24, %25, %26, %27, %28, %29, %30, %31, %32, %33, %34, %35, %36, %37, %38, %39, %40, %41, %42, %43, %44, %45, %46, %47, %48, %49, %50, %51, %52, %53, %54, %55, %56, %57, %58, %59, %60, %61, %62, %63, %64, %65, %66, %67, %68, %69, %70, %71, %72, %73, %74, %75, %76, %77, %78, %79, %80, %81, %82, %83, %84, %85, %86, %87, %88, %89, %90, %91, %92, %93, %94, %95, %96, %97, %98, %99, %100, %101, %102, %103, %104, %105, %106, %107, %108, %109, %110, %111, %112, %113, %114, %115, %116, %117, %118, %119, %120, %121, %122, %123, %124, %125, %126, %127}, %128, %129, p, 1, 1, 0, 1;\n}\n"
    : "+f"(d[0]), "+f"(d[1]), "+f"(d[2]), "+f"(d[3]), "+f"(d[4]), "+f"(d[5]), "+f"(d[6]), "+f"(d[7]), "+f"(d[8]), "+f"(d[9]), "+f"(d[10]), "+f"(d[11]), "+f"(d[12]), "+f"(d[13]), "+f"(d[14]), "+f"(d[15]), "+f"(d[16]), "+f"(d[17]), "+f"(d[18]), "+f"(d[19]), "+f"(d[20]), "+f"(d[21]), "+f"(d[22]), "+f"(d[23]), "+f"(d[24]), "+f"(d[25]), "+f"(d[26]), "+f"(d[27]), "+f"(d[28]), "+f"(d[29]), "+f"(d[30]), "+f"(d[31]), "+f"(d[32]), "+f"(d[33]), "+f"(d[34]), "+f"(d[35]), "+f"(d[36]), "+f"(d[37]), "+f"(d[38]), "+f"(d[39]), "+f"(d[40]), "+f"(d[41]), "+f"(d[42]), "+f"(d[43]), "+f"(d[44]), "+f"(d[45]), "+f"(d[46]), "+f"(d[47]), "+f"(d[48]), "+f"(d[49]), "+f"(d[50]), "+f"(d[51]), "+f"(d[52]), "+f"(d[53]), "+f"(d[54]), "+f"(d[55]), "+f"(d[56]), "+f"(d[57]), "+f"(d[58]), "+f"(d[59]), "+f"(d[60]), "+f"(d[61]), "+f"(d[62]), "+f"(d[63]), "+f"(d[64]), "+f"(d[65]), "+f"(d[66]), "+f"(d[67]), "+f"(d[68]), "+f"(d[69]), "+f"(d[70]), "+f"(d[71]), "+f"(d[72]), "+f"(d[73]), "+f"(d[74]), "+f"(d[75]), "+f"(d[76]), "+f"(d[77]), "+f"(d[78]), "+f"(d[79]), "+f"(d[80]), "+f"(d[81]), "+f"(d[82]), "+f"(d[83]), "+f"(d[84]), "+f"(d[85]), "+f"(d[86]), "+f"(d[87]), "+f"(d[88]), "+f"(d[89]), "+f"(d[90]), "+f"(d[91]), "+f"(d[92]), "+f"(d[93]), "+f"(d[94]), "+f"(d[95]), "+f"(d[96]), "+f"(d[97]), "+f"(d[98]), "+f"(d[99]), "+f"(d[100]), "+f"(d[101]), "+f"(d[102]), "+f"(d[103]), "+f"(d[104]), "+f"(d[105]), "+f"(d[106]), "+f"(d[107]), "+f"(d[108]), "+f"(d[109]), "+f"(d[110]), "+f"(d[111]), "+f"(d[112]), "+f"(d[113]), "+f"(d[114]), "+f"(d[115]), "+f"(d[116]), "+f"(d[117]), "+f"(d[118]), "+f"(d[119]), "+f"(d[120]), "+f"(d[121]), "+f"(d[122]), "+f"(d[123]), "+f"(d[124]), "+f"(d[125]), "+f"(d[126]), "+f"(d[127])
    : "l"(da), "l"(db), "r"(sc));
}
__device__ __forceinline__ void wgmma_m64n128k16_ss(float (&d)[64], uint64_t da, uint64_t db, int sc) {
  asm volatile("{\n.reg .pred p;\nsetp.ne.b32 p, %66, 0;\n"
    "wgmma.mma_async.sync.aligned.m64n128k16.f32.bf16.bf16 {%0, %1, %2, %3, %4, %5, %6, %7, %8, %9, %10, %11, %12, %13, %14, %15, %16, %17, %18, %19, %20, %21, %22, %23, %24, %25, %26, %27, %28, %29, %30, %31, %32, %33, %34, %35, %36, %37, %38, %39, %40, %41, %42, %43, %44, %45, %46, %47, %48, %49, %50, %51, %52, %53, %54, %55, %56, %57, %58, %59, %60, %61, %62, %63}, %64, %65, p, 1, 1, 0, 0;\n}\n"
    : "+f"(d[0]), "+f"(d[1]), "+f"(d[2]), "+f"(d[3]), "+f"(d[4]), "+f"(d[5]), "+f"(d[6]), "+f"(d[7]), "+f"(d[8]), "+f"(d[9]), "+f"(d[10]), "+f"(d[11]), "+f"(d[12]), "+f"(d[13]), "+f"(d[14]), "+f"(d[15]), "+f"(d[16]), "+f"(d[17]), "+f"(d[18]), "+f"(d[19]), "+f"(d[20]), "+f"(d[21]), "+f"(d[22]), "+f"(d[23]), "+f"(d[24]), "+f"(d[25]), "+f"(d[26]), "+f"(d[27]), "+f"(d[28]), "+f"(d[29]), "+f"(d[30]), "+f"(d[31]), "+f"(d[32]), "+f"(d[33]), "+f"(d[34]), "+f"(d[35]), "+f"(d[36]), "+f"(d[37]), "+f"(d[38]), "+f"(d[39]), "+f"(d[40]), "+f"(d[41]), "+f"(d[42]), "+f"(d[43]), "+f"(d[44]), "+f"(d[45]), "+f"(d[46]), "+f"(d[47]), "+f"(d[48]), "+f"(d[49]), "+f"(d[50]), "+f"(d[51]), "+f"(d[52]), "+f"(d[53]), "+f"(d[54]), "+f"(d[55]), "+f"(d[56]), "+f"(d[57]), "+f"(d[58]), "+f"(d[59]), "+f"(d[60]), "+f"(d[61]), "+f"(d[62]), "+f"(d[63])
    : "l"(da), "l"(db), "r"(sc));
}
__device__ __forceinline__ void wgmma_m64n256k16_rs_tb(float (&d)[128], uint32_t a0, uint32_t a1, uint32_t a2, uint32_t a3, uint64_t db, int sc) {
  asm volatile("{\n.reg .pred p;\nsetp.ne.b32 p, %133, 0;\n"
    "wgmma.mma_async.sync.aligned.m64n256k16.f32.bf16.bf16 {%0, %1, %2, %3, %4, %5, %6, %7, %8, %9, %10, %11, %12, %13, %14, %15, %16, %17, %18, %19, %20, %21, %22, %23, %24, %25, %26, %27, %28, %29, %30, %31, %32, %33, %34, %35, %36, %37, %38, %39, %40, %41, %42, %43, %44, %45, %46, %47, %48, %49, %50, %51, %52, %53, %54, %55, %56, %57, %58, %59, %60, %61, %62, %63, %64, %65, %66, %67, %68, %69, %70, %71, %72, %73, %74, %75, %76, %77, %78, %79, %80, %81, %82, %83, %84, %85, %86, %87, %88, %89, %90, %91, %92, %93, %94, %95, %96, %97, %98, %99, %100, %101, %102, %103, %104, %105, %106, %107, %108, %109, %110, %111, %112, %113, %114, %115, %116, %117, %118, %119, %120, %121, %122, %123, %124, %125, %126, %127}, {%128, %129, %130, %131}, %132, p, 1, 1, 1;\n}\n"
    : "+f"(d[0]), "+f"(d[1]), "+f"(d[2]), "+f"(d[3]), "+f"(d[4]), "+f"(d[5]), "+f"(d[6]), "+f"(d[7]), "+f"(d[8]), "+f"(d[9]), "+f"(d[10]), "+f"(d[11]), "+f"(d[12]), "+f"(d[13]), "+f"(d[14]), "+f"(d[15]), "+f"(d[16]), "+f"(d[17]), "+f"(d[18]), "+f"(d[19]), "+f"(d[20]), "+f"(d[21]), "+f"(d[22]), "+f"(d[23]), "+f"(d[24]), "+f"(d[25]), "+f"(d[26]), "+f"(d[27]), "+f"(d[28]), "+f"(d[29]), "+f"(d[30]), "+f"(d[31]), "+f"(d[32]), "+f"(d[33]), "+f"(d[34]), "+f"(d[35]), "+f"(d[36]), "+f"(d[37]), "+f"(d[38]), "+f"(d[39]), "+f"(d[40]), "+f"(d[41]), "+f"(d[42]), "+f"(d[43]), "+f"(d[44]), "+f"(d[45]), "+f"(d[46]), "+f"(d[47]), "+f"(d[48]), "+f"(d[49]), "+f"(d[50]), "+f"(d[51]), "+f"(d[52]), "+f"(d[53]), "+f"(d[54]), "+f"(d[55]), "+f"(d[56]), "+f"(d[57]), "+f"(d[58]), "+f"(d[59]), "+f"(d[60]), "+f"(d[61]), "+f"(d[62]), "+f"(d[63]), "+f"(d[64]), "+f"(d[65]), "+f"(d[66]), "+f"(d[67]), "+f"(d[68]), "+f"(d[69]), "+f"(d[70]), "+f"(d[71]), "+f"(d[72]), "+f"(d[73]), "+f"(d[74]), "+f"(d[75]), "+f"(d[76]), "+f"(d[77]), "+f"(d[78]), "+f"(d[79]), "+f"(d[80]), "+f"(d[81]), "+f"(d[82]), "+f"(d[83]), "+f"(d[84]), "+f"(d[85]), "+f"(d[86]), "+f"(d[87]), "+f"(d[88]), "+f"(d[89]), "+f"(d[90]), "+f"(d[91]), "+f"(d[92]), "+f"(d[93]), "+f"(d[94]), "+f"(d[95]), "+f"(d[96]), "+f"(d[97]), "+f"(d[98]), "+f"(d[99]), "+f"(d[100]), "+f"(d[101]), "+f"(d[102]), "+f"(d[103]), "+f"(d[104]), "+f"(d[105]), "+f"(d[106]), "+f"(d[107]), "+f"(d[108]), "+f"(d[109]), "+f"(d[110]), "+f"(d[111]), "+f"(d[112]), "+f"(d[113]), "+f"(d[114]), "+f"(d[115]), "+f"(d[116]), "+f"(d[117]), "+f"(d[118]), "+f"(d[119]), "+f"(d[120]), "+f"(d[121]), "+f"(d[122]), "+f"(d[123]), "+f"(d[124]), "+f"(d[125]), "+f"(d[126]), "+f"(d[127])
    : "r"(a0), "r"(a1), "r"(a2), "r"(a3), "l"(db), "r"(sc));
}
__device__ __forceinline__ void wgmma_m64n128k16_ss_tb(float (&d)[64], uint64_t da, uint64_t db, int sc) {
  asm volatile("{\n.reg .pred p;\nsetp.ne.b32 p, %66, 0;\n"
    "wgmma.mma_async.sync.aligned.m64n128k16.f32.bf16.bf16 {%0, %1, %2, %3, %4, %5, %6, %7, %8, %9, %10, %11, %12, %13, %14, %15, %16, %17, %18, %19, %20, %21, %22, %23, %24, %25, %26, %27, %28, %29, %30, %31, %32, %33, %34, %35, %36, %37, %38, %39, %40, %41, %42, %43, %44, %45, %46, %47, %48, %49, %50, %51, %52, %53, %54, %55, %56, %57, %58, %59, %60, %61, %62, %63}, %64, %65, p, 1, 1, 0, 1;\n}\n"
    : "+f"(d[0]), "+f"(d[1]), "+f"(d[2]), "+f"(d[3]), "+f"(d[4]), "+f"(d[5]), "+f"(d[6]), "+f"(d[7]), "+f"(d[8]), "+f"(d[9]), "+f"(d[10]), "+f"(d[11]), "+f"(d[12]), "+f"(d[13]), "+f"(d[14]), "+f"(d[15]), "+f"(d[16]), "+f"(d[17]), "+f"(d[18]), "+f"(d[19]), "+f"(d[20]), "+f"(d[21]), "+f"(d[22]), "+f"(d[23]), "+f"(d[24]), "+f"(d[25]), "+f"(d[26]), "+f"(d[27]), "+f"(d[28]), "+f"(d[29]), "+f"(d[30]), "+f"(d[31]), "+f"(d[32]), "+f"(d[33]), "+f"(d[34]), "+f"(d[35]), "+f"(d[36]), "+f"(d[37]), "+f"(d[38]), "+f"(d[39]), "+f"(d[40]), "+f"(d[41]), "+f"(d[42]), "+f"(d[43]), "+f"(d[44]), "+f"(d[45]), "+f"(d[46]), "+f"(d[47]), "+f"(d[48]), "+f"(d[49]), "+f"(d[50]), "+f"(d[51]), "+f"(d[52]), "+f"(d[53]), "+f"(d[54]), "+f"(d[55]), "+f"(d[56]), "+f"(d[57]), "+f"(d[58]), "+f"(d[59]), "+f"(d[60]), "+f"(d[61]), "+f"(d[62]), "+f"(d[63])
    : "l"(da), "l"(db), "r"(sc));
}
__device__ __forceinline__ void wgmma_m64n128k16_rs_tb(float (&d)[64], uint32_t a0, uint32_t a1, uint32_t a2, uint32_t a3, uint64_t db, int sc) {
  asm volatile("{\n.reg .pred p;\nsetp.ne.b32 p, %69, 0;\n"
    "wgmma.mma_async.sync.aligned.m64n128k16.f32.bf16.bf16 {%0, %1, %2, %3, %4, %5, %6, %7, %8, %9, %10, %11, %12, %13, %14, %15, %16, %17, %18, %19, %20, %21, %22, %23, %24, %25, %26, %27, %28, %29, %30, %31, %32, %33, %34, %35, %36, %37, %38, %39, %40, %41, %42, %43, %44, %45, %46, %47, %48, %49, %50, %51, %52, %53, %54, %55, %56, %57, %58, %59, %60, %61, %62, %63}, {%64, %65, %66, %67}, %68, p, 1, 1, 1;\n}\n"
    : "+f"(d[0]), "+f"(d[1]), "+f"(d[2]), "+f"(d[3]), "+f"(d[4]), "+f"(d[5]), "+f"(d[6]), "+f"(d[7]), "+f"(d[8]), "+f"(d[9]), "+f"(d[10]), "+f"(d[11]), "+f"(d[12]), "+f"(d[13]), "+f"(d[14]), "+f"(d[15]), "+f"(d[16]), "+f"(d[17]), "+f"(d[18]), "+f"(d[19]), "+f"(d[20]), "+f"(d[21]), "+f"(d[22]), "+f"(d[23]), "+f"(d[24]), "+f"(d[25]), "+f"(d[26]), "+f"(d[27]), "+f"(d[28]), "+f"(d[29]), "+f"(d[30]), "+f"(d[31]), "+f"(d[32]), "+f"(d[33]), "+f"(d[34]), "+f"(d[35]), "+f"(d[36]), "+f"(d[37]), "+f"(d[38]), "+f"(d[39]), "+f"(d[40]), "+f"(d[41]), "+f"(d[42]), "+f"(d[43]), "+f"(d[44]), "+f"(d[45]), "+f"(d[46]), "+f"(d[47]), "+f"(d[48]), "+f"(d[49]), "+f"(d[50]), "+f"(d[51]), "+f"(d[52]), "+f"(d[53]), "+f"(d[54]), "+f"(d[55]), "+f"(d[56]), "+f"(d[57]), "+f"(d[58]), "+f"(d[59]), "+f"(d[60]), "+f"(d[61]), "+f"(d[62]), "+f"(d[63])
    : "r"(a0), "r"(a1), "r"(a2), "r"(a3), "l"(db), "r"(sc));
}
__device__ __forceinline__ void wgmma_m64n64k16_ss_tb(float (&d)[32], uint64_t da, uint64_t db, int sc) {
  asm volatile("{\n.reg .pred p;\nsetp.ne.b32 p, %34, 0;\n"
    "wgmma.mma_async.sync.aligned.m64n64k16.f32.bf16.bf16 {%0, %1, %2, %3, %4, %5, %6, %7, %8, %9, %10, %11, %12, %13, %14, %15, %16, %17, %18, %19, %20, %21, %22, %23, %24, %25, %26, %27, %28, %29, %30, %31}, %32, %33, p, 1, 1, 0, 1;\n}\n"
    : "+f"(d[0]), "+f"(d[1]), "+f"(d[2]), "+f"(d[3]), "+f"(d[4]), "+f"(d[5]), "+f"(d[6]), "+f"(d[7]), "+f"(d[8]), "+f"(d[9]), "+f"(d[10]), "+f"(d[11]), "+f"(d[12]), "+f"(d[13]), "+f"(d[14]), "+f"(d[15]), "+f"(d[16]), "+f"(d[17]), "+f"(d[18]), "+f"(d[19]), "+f"(d[20]), "+f"(d[21]), "+f"(d[22]), "+f"(d[23]), "+f"(d[24]), "+f"(d[25]), "+f"(d[26]), "+f"(d[27]), "+f"(d[28]), "+f"(d[29]), "+f"(d[30]), "+f"(d[31])
    : "l"(da), "l"(db), "r"(sc));
}
__device__ __forceinline__ void wgmma_m64n64k16_rs_tb(float (&d)[32], uint32_t a0, uint32_t a1, uint32_t a2, uint32_t a3, uint64_t db, int sc) {
  asm volatile("{\n.reg .pred p;\nsetp.ne.b32 p, %37, 0;\n"
    "wgmma.mma_async.sync.aligned.m64n64k16.f32.bf16.bf16 {%0, %1, %2, %3, %4, %5, %6, %7, %8, %9, %10, %11, %12, %13, %14, %15, %16, %17, %18, %19, %20, %21, %22, %23, %24, %25, %26, %27, %28, %29, %30, %31}, {%32, %33, %34, %35}, %36, p, 1, 1, 1;\n}\n"
    : "+f"(d[0]), "+f"(d[1]), "+f"(d[2]), "+f"(d[3]), "+f"(d[4]), "+f"(d[5]), "+f"(d[6]), "+f"(d[7]), "+f"(d[8]), "+f"(d[9]), "+f"(d[10]), "+f"(d[11]), "+f"(d[12]), "+f"(d[13]), "+f"(d[14]), "+f"(d[15]), "+f"(d[16]), "+f"(d[17]), "+f"(d[18]), "+f"(d[19]), "+f"(d[20]), "+f"(d[21]), "+f"(d[22]), "+f"(d[23]), "+f"(d[24]), "+f"(d[25]), "+f"(d[26]), "+f"(d[27]), "+f"(d[28]), "+f"(d[29]), "+f"(d[30]), "+f"(d[31])
    : "r"(a0), "r"(a1), "r"(a2), "r"(a3), "l"(db), "r"(sc));
}
__device__ __forceinline__ void wgmma_m64n192k16_ss_tb(float (&d)[128], uint64_t da, uint64_t db, int sc) {
  asm volatile("{\n.reg .pred p;\nsetp.ne.b32 p, %98, 0;\n"
    "wgmma.mma_async.sync.aligned.m64n192k16.f32.bf16.bf16 {%0, %1, %2, %3, %4, %5, %6, %7, %8, %9, %10, %11, %12, %13, %14, %15, %16, %17, %18, %19, %20, %21, %22, %23, %24, %25, %26, %27, %28, %29, %30, %31, %32, %33, %34, %35, %36, %37, %38, %39, %40, %41, %42, %43, %44, %45, %46, %47, %48, %49, %50, %51, %52, %53, %54, %55, %56, %57, %58, %59, %60, %61, %62, %63, %64, %65, %66, %67, %68, %69, %70, %71, %72, %73, %74, %75, %76, %77, %78, %79, %80, %81, %82, %83, %84, %85, %86, %87, %88, %89, %90, %91, %92, %93, %94, %95}, %96, %97, p, 1, 1, 0, 1;\n}\n"
    : "+f"(d[0]), "+f"(d[1]), "+f"(d[2]), "+f"(d[3]), "+f"(d[4]), "+f"(d[5]), "+f"(d[6]), "+f"(d[7]), "+f"(d[8]), "+f"(d[9]), "+f"(d[10]), "+f"(d[11]), "+f"(d[12]), "+f"(d[13]), "+f"(d[14]), "+f"(d[15]), "+f"(d[16]), "+f"(d[17]), "+f"(d[18]), "+f"(d[19]), "+f"(d[20]), "+f"(d[21]), "+f"(d[22]), "+f"(d[23]), "+f"(d[24]), "+f"(d[25]), "+f"(d[26]), "+f"(d[27]), "+f"(d[28]), "+f"(d[29]), "+f"(d[30]), "+f"(d[31]), "+f"(d[32]), "+f"(d[33]), "+f"(d[34]), "+f"(d[35]), "+f"(d[36]), "+f"(d[37]), "+f"(d[38]), "+f"(d[39]), "+f"(d[40]), "+f"(d[41]), "+f"(d[42]), "+f"(d[43]), "+f"(d[44]), "+f"(d[45]), "+f"(d[46]), "+f"(d[47]), "+f"(d[48]), "+f"(d[49]), "+f"(d[50]), "+f"(d[51]), "+f"(d[52]), "+f"(d[53]), "+f"(d[54]), "+f"(d[55]), "+f"(d[56]), "+f"(d[57]), "+f"(d[58]), "+f"(d[59]), "+f"(d[60]), "+f"(d[61]), "+f"(d[62]), "+f"(d[63]), "+f"(d[64]), "+f"(d[65]), "+f"(d[66]), "+f"(d[67]), "+f"(d[68]), "+f"(d[69]), "+f"(d[70]), "+f"(d[71]), "+f"(d[72]), "+f"(d[73]), "+f"(d[74]), "+f"(d[75]), "+f"(d[76]), "+f"(d[77]), "+f"(d[78]), "+f"(d[79]), "+f"(d[80]), "+f"(d[81]), "+f"(d[82]), "+f"(d[83]), "+f"(d[84]), "+f"(d[85]), "+f"(d[86]), "+f"(d[87]), "+f"(d[88]), "+f"(d[89]), "+f"(d[90]), "+f"(d[91]), "+f"(d[92]), "+f"(d[93]), "+f"(d[94]), "+f"(d[95])
    : "l"(da), "l"(db), "r"(sc));
}

#define TM(id)
#define GT_MIN(i)
#define GT_MAX(i)

constexpr int NS = 5;
constexpr uint32_t STG = 32768;
constexpr uint32_t SM_Q = 0;
constexpr uint32_t SM_RING = 65536;
constexpr uint32_t SM_BAR = SM_RING + NS * STG;
constexpr uint32_t SM_TOTAL = SM_BAR + 256 + 1024;

struct Ring {
  uint32_t base, full0, empty0, st, ph, nst, stg;
  __device__ __forceinline__ void init(uint32_t sb) { base = sb + SM_RING; full0 = sb + SM_BAR; empty0 = sb + SM_BAR + 64; st = 0; ph = 0; nst = NS; stg = STG; }
  __device__ __forceinline__ uint32_t phase() const { return (ph >> st) & 1; }
  __device__ __forceinline__ uint32_t buf() const { return base + st * stg; }
  __device__ __forceinline__ uint32_t full() const { return full0 + st * 8; }
  __device__ __forceinline__ uint32_t empty() const { return empty0 + st * 8; }
  __device__ __forceinline__ void next() { ph ^= 1u << st; st = (st + 1 >= nst) ? 0 : st + 1; }
  __device__ __forceinline__ void shrink() { nst = NS - 1; if (st >= nst) st = 0; }
  __device__ __forceinline__ uint32_t acquire(uint32_t bytes) {
    mbar_wait(empty(), phase() ^ 1); mbar_expect_tx(full(), bytes); return buf();
  }
  __device__ __forceinline__ uint32_t wait() { mbar_wait(full(), phase()); return buf(); }
};
template <int CL = 2>
__device__ __forceinline__ void ring_release(uint32_t empty_bar, int lane) {
  __syncwarp();
  if (lane < CL) mbar_arrive_remote(empty_bar, (uint32_t)lane);
}

template <int CL>
__device__ __forceinline__ void gemm_k448_n256(Ring& r, float (&acc)[128], int wg, int lane) {
  uint32_t hb = 0, hrel = 0, prel = 0, phrel = 0;
#pragma unroll
  for (int c = 0; c < 7; ++c) {
    if ((c & 1) == 0) { hb = r.wait(); hrel = r.empty(); r.next(); }
    uint32_t wb = r.wait(); uint32_t wrel = r.empty(); r.next();
    uint64_t da = mk_desc(hb + (c & 1) * 16384 + wg * 8192, 16, 1024);
    uint64_t db = mk_desc(wb, 8192, 1024);
    wg_fence();
#pragma unroll
    for (int k = 0; k < 4; ++k) wgmma_m64n256k16_ss_tb(acc, da + k * 2, db + k * 128, (c | k) != 0);
    wg_commit();
    if (c > 0) {
      wg_wait<1>();
      ring_release<CL>(prel, lane);
      if ((c & 1) == 0) ring_release<CL>(phrel, lane);
    }
    prel = wrel; phrel = hrel;
  }
  wg_wait<0>();
  ring_release<CL>(prel, lane); ring_release<CL>(phrel, lane);
}

template <bool RELU>
__device__ __forceinline__ void store_tile_bf16(uint32_t base, const float (&acc)[128], int rloc, int t4) {
  uint32_t row0 = base + rloc * 128, row1 = row0 + 8 * 128;
  uint32_t sw = (uint32_t)(rloc & 7);
#pragma unroll
  for (int j = 0; j < 32; ++j) {
    uint32_t off = (uint32_t)(j >> 3) * 16384 + ((((uint32_t)j & 7) ^ sw) << 4) + t4 * 4;
    float a = acc[4 * j], b = acc[4 * j + 1], c = acc[4 * j + 2], d = acc[4 * j + 3];
    if (RELU) { a = fmaxf(a, 0.f); b = fmaxf(b, 0.f); c = fmaxf(c, 0.f); d = fmaxf(d, 0.f); }
    asm volatile("st.shared.b32 [%0], %1;" ::"r"(row0 + off), "r"(pack_bf16(a, b)) : "memory");
    asm volatile("st.shared.b32 [%0], %1;" ::"r"(row1 + off), "r"(pack_bf16(c, d)) : "memory");
  }
}

template <int NJ, int OFF = 0, int SZ = 64, bool WAIT = true>
__device__ __forceinline__ void red_rows(uint32_t stg, const CUtensorMap* tm, int row0, int col0, const float (&a)[SZ], int sel, int lane) {
  asm volatile("" : "+r"(stg), "+r"(lane));
  if (WAIT) {
    if (lane == 0) asm volatile("cp.async.bulk.wait_group.read 0;" ::: "memory");
    __syncwarp();
  }
  const uint32_t g = lane >> 2, t4 = lane & 3;
  const uint32_t wbase = stg + g * 128 + (t4 & 1) * 8;
#pragma unroll
  for (int j = 0; j < NJ; ++j)
    asm volatile("st.shared.v2.f32 [%0], {%1, %2};" ::"r"(wbase + (j >> 2) * 1024 + ((((j & 3) * 2 + (t4 >> 1)) ^ g) << 4)),
                 "f"(a[OFF + 4 * j + sel]), "f"(a[OFF + 4 * j + sel + 1]) : "memory");
  fence_async_smem();
  __syncwarp();
  if (lane == 0) {
#pragma unroll
    for (int b = 0; b < NJ / 4; ++b)
      asm volatile("cp.reduce.async.bulk.tensor.2d.global.shared::cta.add.tile.bulk_group [%0, {%2, %3}], [%1];"
                   ::"l"(tm), "r"(stg + b * 1024), "r"(col0 + b * 32), "r"(row0) : "memory");
    asm volatile("cp.async.bulk.commit_group;" ::: "memory");
  }
}

template <int NSM, int NRG, int CL>
__device__ __forceinline__ void out_proj(Ring& r, const uint32_t (&ob)[64], uint32_t abase,
                                         const CUtensorMap* tm, int roww, uint32_t stg, int lane) {
  constexpr int NST = (NSM + NRG) / 2;
  uint32_t prel = 0;
  float accA[64], accB[64];
  float(&cur32)[32] = *reinterpret_cast<float(*)[32]>(&accB[0]);
#pragma unroll
  for (int pass = 0; pass < 4; ++pass) {
    float(&cur)[64] = (pass & 1) ? accB : accA;
    float(&prv)[64] = (pass & 1) ? accA : accB;
#pragma unroll
    for (int st = 0; st < NST; ++st) {
      uint32_t wb = r.wait(); uint32_t rel = r.empty(); r.next();
      asm volatile("" : "+r"(abase));
      wg_fence();
#pragma unroll
      for (int cc = 0; cc < 2; ++cc) {
        const int c = 2 * st + cc;
#pragma unroll
        for (int k = 0; k < 4; ++k) {
          const int sc = (c | k) != 0;
          if (pass < 3) {
            uint64_t db = mk_desc(wb + cc * 16384 + k * 2048, 8192, 1024);
            if (c < NSM) wgmma_m64n128k16_ss_tb(cur, mk_desc(abase + c * 16384 + k * 32, 16, 1024), db, sc);
            else { const int o = (c - NSM) * 16 + 4 * k; wgmma_m64n128k16_rs_tb(cur, ob[o], ob[o + 1], ob[o + 2], ob[o + 3], db, sc); }
          } else {
            uint64_t db = mk_desc(wb + cc * 8192 + k * 2048, 8192, 1024);
            if (c < NSM) wgmma_m64n64k16_ss_tb(cur32, mk_desc(abase + c * 16384 + k * 32, 16, 1024), db, sc);
            else { const int o = (c - NSM) * 16 + 4 * k; wgmma_m64n64k16_rs_tb(cur32, ob[o], ob[o + 1], ob[o + 2], ob[o + 3], db, sc); }
          }
        }
      }
      wg_commit();
      if (pass | st) { wg_wait<1>(); ring_release<CL>(prel, lane); }
      prel = rel;
      if (pass > 0) {
        if (st == 0) red_rows<16>(stg, tm, roww, (pass - 1) * 128, prv, 0, lane);
        if (st == NST / 2) red_rows<16>(stg, tm, roww + 8, (pass - 1) * 128, prv, 2, lane);
      }
    }
  }
  wg_wait<0>(); ring_release<CL>(prel, lane);
  red_rows<8>(stg, tm, roww, 384, accB, 0, lane);
  red_rows<8>(stg, tm, roww + 8, 384, accB, 2, lane);
  if (lane == 0) asm volatile("cp.async.bulk.wait_group 0;" ::: "memory");
}
template <int CL>
__device__ __forceinline__ void out_proj_loads(Ring& r, const CUtensorMap* tm, int krow0, int nch, uint32_t rank) {
  r.shrink();
  constexpr uint16_t MASK = (1 << CL) - 1;
  for (int pass = 0; pass < 4; ++pass)
    for (int st = 0; st < nch / 2; ++st) {
      if (pass < 3) {
        uint32_t b = r.acquire(32768);
        for (int x = 0; x < 4 / CL; ++x) {
          const int bx = rank * (4 / CL) + x;
          tma_load_mc(b + bx * 8192, tm, pass * 128 + (bx & 1) * 64, krow0 + (2 * st + (bx >> 1)) * 64, r.full(), MASK);
        }
      } else {
        uint32_t b = r.acquire(16384);
        if (CL == 1) { for (int x = 0; x < 2; ++x) tma_load_mc(b + x * 8192, tm, 384, krow0 + (2 * st + x) * 64, r.full(), MASK); }
        else if (rank < 2) tma_load_mc(b + rank * 8192, tm, 384, krow0 + (2 * st + rank) * 64, r.full(), MASK);
      }
      r.next();
    }
}

#define ACL 2
__global__ void __cluster_dims__(ACL, 1, 1) __launch_bounds__(384, 1)
attn_kernel(const __grid_constant__ CUtensorMap tm_h, const __grid_constant__ CUtensorMap tm_wq,
            const __grid_constant__ CUtensorMap tm_k, const __grid_constant__ CUtensorMap tm_v,
            const __grid_constant__ CUtensorMap tm_wo, const __grid_constant__ CUtensorMap tm_oA,
            const __grid_constant__ CUtensorMap tm_oAs, const __grid_constant__ CUtensorMap tm_acc) {
  extern __shared__ uint8_t smem_raw[];
  const uint32_t sb = (smem_u32(smem_raw) + 1023) & ~1023u;
  const int tid = threadIdx.x, wg = tid >> 7, lane = tid & 31;
  const int qt = blockIdx.x, kvh = blockIdx.y;
  const uint32_t rank = cluster_rank();
  Ring r; r.init(sb);
  const uint32_t bar_oA = sb + SM_BAR + 128, bar_oAf = sb + SM_BAR + 136;
  if (tid == 0) {
    for (int i = 0; i < NS; ++i) { mbar_init(r.full0 + 8 * i, 1); mbar_init(r.empty0 + 8 * i, 8 * ACL); }
    mbar_init(bar_oA, 256); mbar_init(bar_oAf, 1);
    asm volatile("fence.mbarrier_init.release.cluster;" ::: "memory");
  }
  cluster_sync_all();
  pdl_wait();
  GT_MIN(4);

  if (wg == 2) {
    asm volatile("setmaxnreg.dec.sync.aligned.u32 24;");
    if (tid == 256) {
      const int krow0 = kvh * SKV + (SKV - WIN);
      for (int hh = 0; hh < 2; ++hh) {
        const int head = kvh * 2 + hh;
        for (int p = 0; p < 4; ++p) {
          int nc = (p < 3) ? 2 : 1;
          uint32_t b = r.acquire(nc * 16384);
          for (int c = 0; c < nc; ++c) tma_load(b + c * 16384, &tm_h, (2 * p + c) * 64, qt * 128, r.full());
          r.next();
          for (int c = 0; c < nc; ++c) {
            b = r.acquire(32768);
            for (int x = 0; x < 4 / ACL; ++x) {
              int bx = rank * 2 + x;
              tma_load_mc(b + bx * 8192, &tm_wq, head * 256 + bx * 64, (2 * p + c) * 64, r.full(), (1 << ACL) - 1);
            }
            r.next();
          }
        }
        for (int t = 0; t < 4; ++t) {
          for (int hf = 0; hf < 2; ++hf) {
            uint32_t b = r.acquire(32768);
            for (int x = 0; x < 2 / ACL; ++x)
              tma_load_mc(b + (rank + x) * 16384, &tm_k, (2 * hf + rank + x) * 64, krow0 + t * 128, r.full(), (1 << ACL) - 1);
            r.next();
          }
          for (int hf = 0; hf < 2; ++hf) {
            uint32_t b = r.acquire(32768);
            for (int x = 0; x < 4 / ACL; ++x) {
              int bx = rank * 2 + x;
              tma_load_mc(b + bx * 8192, &tm_v, bx * 64, krow0 + t * 128 + hf * 64, r.full(), (1 << ACL) - 1);
            }
            r.next();
          }
        }
      }
      mbar_wait(bar_oA, 0);
      mbar_expect_tx(bar_oAf, 65536);
      for (int c = 0; c < 4; ++c) tma_load(sb + SM_Q + c * 16384, &tm_oA, c * 64, kvh * SEQ + qt * 128, bar_oAf);
      out_proj_loads<ACL>(r, &tm_wo, kvh * 512, 8, rank);
    }
  } else {
    asm volatile("setmaxnreg.inc.sync.aligned.u32 240;");
    const int warp = (tid >> 5) & 3, g = lane >> 2, t4 = lane & 3;
    const int rloc = wg * 64 + warp * 16 + g;
    uint32_t ob[64];
    float acc[128];
    const float CS = 1.4426950408889634f * 0.0625f;
    TM(0);
#pragma unroll 1
    for (int hh = 0; hh < 2; ++hh) {
      gemm_k448_n256<ACL>(r, acc, wg, lane);
      TM(1);
      if (hh == 1) {
        if ((tid & 127) == 0) asm volatile("cp.async.bulk.wait_group.read 0;" ::: "memory");
        bar_sync(1 + wg, 128);
      }
      store_tile_bf16<false>(sb + SM_Q, acc, rloc, t4);
      fence_async_smem();
      bar_sync(1 + wg, 128);
      float m0 = -INFINITY, m1 = -INFINITY, l0 = 0.f, l1 = 0.f;
      const uint32_t qa0 = sb + SM_Q + wg * 8192;
      if (wg == 1) bar_arrive(3, 256);
      TM(2);
      bar_sync(3 + wg, 256);
#pragma unroll 1
      for (int t = 0; t < 4; ++t) {
        float s[64];
        TM(3);
        {
          uint32_t qa = qa0; asm volatile("" : "+r"(qa));
          uint32_t ka = r.wait(); uint32_t rel0 = r.empty(); r.next();
          wg_fence();
#pragma unroll
          for (int k = 0; k < 8; ++k)
            wgmma_m64n128k16_ss(s, mk_desc(qa + (k >> 2) * 16384 + (k & 3) * 32, 16, 1024),
                                mk_desc(ka + (k >> 2) * 16384 + (k & 3) * 32, 16, 1024), k != 0);
          wg_commit();
          uint32_t kb = r.wait(); uint32_t rel1 = r.empty(); r.next();
          wg_fence();
#pragma unroll
          for (int k = 0; k < 8; ++k)
            wgmma_m64n128k16_ss(s, mk_desc(qa + (2 + (k >> 2)) * 16384 + (k & 3) * 32, 16, 1024),
                                mk_desc(kb + (k >> 2) * 16384 + (k & 3) * 32, 16, 1024), 1);
          wg_commit();
          bar_arrive(4 - wg, 256);
          wg_wait<1>(); ring_release<ACL>(rel0, lane);
          wg_wait<0>(); ring_release<ACL>(rel1, lane);
        }
        TM(4);
        float mx0 = m0, mx1 = m1;
#pragma unroll
        for (int j = 0; j < 16; ++j) {
          uint32_t a = pack_bf16(s[4 * j], s[4 * j + 1]), b = pack_bf16(s[4 * j + 2], s[4 * j + 3]);
          s[4 * j] = bf_lo(a); s[4 * j + 1] = bf_hi(a); s[4 * j + 2] = bf_lo(b); s[4 * j + 3] = bf_hi(b);
          mx0 = fmaxf(mx0, fmaxf(s[4 * j], s[4 * j + 1])); mx1 = fmaxf(mx1, fmaxf(s[4 * j + 2], s[4 * j + 3]));
        }
        mx0 = fmaxf(mx0, __shfl_xor_sync(0xffffffffu, mx0, 1)); mx0 = fmaxf(mx0, __shfl_xor_sync(0xffffffffu, mx0, 2));
        mx1 = fmaxf(mx1, __shfl_xor_sync(0xffffffffu, mx1, 1)); mx1 = fmaxf(mx1, __shfl_xor_sync(0xffffffffu, mx1, 2));
        const float c0 = ex2((m0 - mx0) * CS), c1 = ex2((m1 - mx1) * CS);
        m0 = mx0; m1 = mx1;
        const float nb0 = -mx0 * CS, nb1 = -mx1 * CS;
        float ps0 = 0.f, ps1 = 0.f;
        uint32_t pa[32];
#pragma unroll
        for (int j = 0; j < 16; ++j) {
          float e0 = ex2(fmaf(s[4 * j], CS, nb0)), e1 = ex2(fmaf(s[4 * j + 1], CS, nb0));
          float e2 = ex2(fmaf(s[4 * j + 2], CS, nb1)), e3 = ex2(fmaf(s[4 * j + 3], CS, nb1));
          ps0 += e0 + e1; ps1 += e2 + e3;
          pa[2 * j] = pack_bf16(e0, e1); pa[2 * j + 1] = pack_bf16(e2, e3);
        }
        l0 = l0 * c0 + ps0; l1 = l1 * c1 + ps1;
        if (t > 0) {
#pragma unroll
          for (int j = 0; j < 32; ++j) { acc[4 * j] *= c0; acc[4 * j + 1] *= c0; acc[4 * j + 2] *= c1; acc[4 * j + 3] *= c1; }
        }
#pragma unroll
        for (int j = 0; j < 32; ++j) asm volatile("" : "+r"(pa[j]));
#pragma unroll
        for (int j = 0; j < 128; ++j) asm volatile("" : "+f"(acc[j]));
        asm volatile("" : "+f"(l0), "+f"(l1));
        TM(5);
        bar_sync(3 + wg, 256);
        TM(6);
        {
          uint32_t va = r.wait(); uint32_t rel0 = r.empty(); r.next();
          wg_fence();
#pragma unroll
          for (int k = 0; k < 4; ++k)
            wgmma_m64n256k16_rs_tb(acc, pa[4 * k], pa[4 * k + 1], pa[4 * k + 2], pa[4 * k + 3],
                                   mk_desc(va + k * 2048, 8192, 1024), (t | k) != 0);
          wg_commit();
          uint32_t vb = r.wait(); uint32_t rel1 = r.empty(); r.next();
          wg_fence();
#pragma unroll
          for (int k = 0; k < 4; ++k)
            wgmma_m64n256k16_rs_tb(acc, pa[16 + 4 * k], pa[16 + 4 * k + 1], pa[16 + 4 * k + 2], pa[16 + 4 * k + 3],
                                   mk_desc(vb + k * 2048, 8192, 1024), 1);
          wg_commit();
          if (t == 3 && wg == 0) bar_arrive(4, 256);
          wg_wait<1>(); ring_release<ACL>(rel0, lane);
          wg_wait<0>(); ring_release<ACL>(rel1, lane);
        }
      }
      TM(7);
      l0 += __shfl_xor_sync(0xffffffffu, l0, 1); l0 += __shfl_xor_sync(0xffffffffu, l0, 2);
      l1 += __shfl_xor_sync(0xffffffffu, l1, 1); l1 += __shfl_xor_sync(0xffffffffu, l1, 2);
      const float i0 = 1.f / l0, i1 = 1.f / l1;
#pragma unroll
      for (int j = 0; j < 32; ++j) {
        ob[2 * j] = pack_bf16(acc[4 * j] * i0, acc[4 * j + 1] * i0);
        ob[2 * j + 1] = pack_bf16(acc[4 * j + 2] * i1, acc[4 * j + 3] * i1);
      }
      if (hh == 0) {
        uint32_t row0 = sb + SM_Q + rloc * 128, row1 = row0 + 8 * 128;
        uint32_t sw = (uint32_t)(rloc & 7);
#pragma unroll
        for (int j = 0; j < 32; ++j) {
          uint32_t off = (uint32_t)(j >> 3) * 16384 + ((((uint32_t)j & 7) ^ sw) << 4) + t4 * 4;
          asm volatile("st.shared.b32 [%0], %1;" ::"r"(row0 + off), "r"(ob[2 * j]) : "memory");
          asm volatile("st.shared.b32 [%0], %1;" ::"r"(row1 + off), "r"(ob[2 * j + 1]) : "memory");
        }
        fence_async_smem();
        bar_sync(1 + wg, 128);
        if ((tid & 127) == 0) {
          for (int c = 0; c < 4; ++c)
            asm volatile("cp.async.bulk.tensor.2d.global.shared::cta.bulk_group [%0, {%2, %3}], [%1];"
                         ::"l"(&tm_oAs), "r"(sb + SM_Q + c * 16384 + wg * 8192), "r"(c * 64), "r"(kvh * SEQ + qt * 128 + wg * 64) : "memory");
          asm volatile("cp.async.bulk.commit_group;" ::: "memory");
        }
      }
    }
    if ((tid & 127) == 0) asm volatile("cp.async.bulk.wait_group 0;" ::: "memory");
    mbar_arrive(bar_oA);
    mbar_wait(bar_oAf, 0);
    TM(8);
    r.shrink();
    out_proj<4, 4, ACL>(r, ob, sb + SM_Q + wg * 8192, &tm_acc, qt * 128 + wg * 64 + warp * 16,
                   sb + SM_RING + (NS - 1) * STG + (wg * 4 + warp) * 4096, lane);
    TM(9);
  }
  cluster_sync_all();
  GT_MAX(5);
}

constexpr uint32_t F_STG = 57344, F_A = 0, F_RING = 57344, F_BAR = F_RING + 3 * F_STG, F_TOTAL = F_BAR + 256 + 1024;

template <int WG>
__device__ __forceinline__ void ffn_gemm(Ring& r, float (&acc)[128], uint32_t abase, int lane) {
  uint32_t prel = 0;
#pragma unroll
  for (int c = 0; c < 7; ++c) {
    uint32_t wb = r.wait(); uint32_t wrel = r.empty(); r.next();
    uint64_t da = mk_desc(abase + c * 8192, 16, 1024);
    uint64_t db = mk_desc(wb + WG * 32768, 8192, 1024);
    wg_fence();
#pragma unroll
    for (int k = 0; k < 4; ++k) {
      if (WG == 0) wgmma_m64n256k16_ss_tb(acc, da + k * 2, db + k * 128, (c | k) != 0);
      else wgmma_m64n192k16_ss_tb(acc, da + k * 2, db + k * 128, (c | k) != 0);
    }
    wg_commit();
    if (c > 0) { wg_wait<1>(); ring_release<2>(prel, lane); }
    prel = wrel;
  }
  wg_wait<0>();
  ring_release<2>(prel, lane);
}

template <int WG>
__device__ __forceinline__ void ffn_consumer(Ring& r, uint32_t sb, uint32_t bar_a, int rt, int warp, int lane, const CUtensorMap* tm) {
  const int g = lane >> 2, t4 = lane & 3, row = warp * 16 + g;
  float acc[128];
  TM(20);
  mbar_wait(bar_a, 0);
  TM(21);
  ffn_gemm<WG>(r, acc, sb + F_A, lane);
  TM(22);
  bar_sync(5, 256);
  {
    uint32_t row0 = sb + F_A + WG * 32768 + row * 128, row1 = row0 + 8 * 128;
    uint32_t sw = (uint32_t)(row & 7);
#pragma unroll
    for (int j = 0; j < (WG == 0 ? 32 : 24); ++j) {
      uint32_t off = (uint32_t)(j >> 3) * 8192 + ((((uint32_t)j & 7) ^ sw) << 4) + t4 * 4;
      asm volatile("st.shared.b32 [%0], %1;" ::"r"(row0 + off), "r"(pack_bf16(fmaxf(acc[4 * j], 0.f), fmaxf(acc[4 * j + 1], 0.f))) : "memory");
      asm volatile("st.shared.b32 [%0], %1;" ::"r"(row1 + off), "r"(pack_bf16(fmaxf(acc[4 * j + 2], 0.f), fmaxf(acc[4 * j + 3], 0.f))) : "memory");
    }
  }
  fence_async_smem();
  bar_sync(5, 256);
  TM(23);
  ffn_gemm<WG>(r, acc, sb + F_A, lane);
  TM(24);
  bar_sync(5, 256);
  const int r0 = rt * 64 + warp * 16, c0 = WG * 256;
  const uint32_t stg = sb + (WG * 4 + warp) * 16384;
  red_rows<16, 0, 128, false>(stg, tm, r0, c0, acc, 0, lane);
  red_rows<16, 0, 128, false>(stg + 4096, tm, r0 + 8, c0, acc, 2, lane);
  if (WG == 0) {
    red_rows<16, 64, 128, false>(stg + 8192, tm, r0, c0 + 128, acc, 0, lane);
    red_rows<16, 64, 128, false>(stg + 12288, tm, r0 + 8, c0 + 128, acc, 2, lane);
  } else {
    red_rows<8, 64, 128, false>(stg + 8192, tm, r0, c0 + 128, acc, 0, lane);
    red_rows<8, 64, 128, false>(stg + 12288, tm, r0 + 8, c0 + 128, acc, 2, lane);
  }
  if (lane == 0) asm volatile("cp.async.bulk.wait_group 0;" ::: "memory");
  TM(25);
}

__global__ void __cluster_dims__(2, 1, 1) __launch_bounds__(384, 1)
ffn_kernel(const __grid_constant__ CUtensorMap tm_h2, const __grid_constant__ CUtensorMap tm_w1,
           const __grid_constant__ CUtensorMap tm_w2, const __grid_constant__ CUtensorMap tm_acc) {
  extern __shared__ uint8_t smem_raw[];
  const uint32_t sb = (smem_u32(smem_raw) + 1023) & ~1023u;
  const int tid = threadIdx.x, wg = tid >> 7, lane = tid & 31;
  const int rt = blockIdx.x, sl = blockIdx.y;
  const uint32_t rank = cluster_rank();
  Ring r; r.base = sb + F_RING; r.full0 = sb + F_BAR; r.empty0 = sb + F_BAR + 64; r.st = 0; r.ph = 0; r.nst = 3; r.stg = F_STG;
  const uint32_t bar_a = sb + F_BAR + 128;
  if (tid == 0) {
    for (int i = 0; i < 3; ++i) { mbar_init(r.full0 + 8 * i, 1); mbar_init(r.empty0 + 8 * i, 16); }
    mbar_init(bar_a, 1);
    asm volatile("fence.mbarrier_init.release.cluster;" ::: "memory");
  }
  cluster_sync_all();
  if (wg == 2) {
    asm volatile("setmaxnreg.dec.sync.aligned.u32 24;");
    if (tid == 256) {
      const int b0 = rank ? 4 : 0, b1 = rank ? 7 : 4;
      pdl_wait();
      mbar_expect_tx(bar_a, 57344);
      for (int k = 0; k < 7; ++k) tma_load(sb + F_A + k * 8192, &tm_h2, k * 64, rt * 64, bar_a);
      for (int c = 0; c < 14; ++c) {
        uint32_t b = r.acquire(F_STG);
        for (int bx = b0; bx < b1; ++bx) {
          if (c < 7) tma_load_mc(b + bx * 8192, &tm_w1, sl * 448 + bx * 64, c * 64, r.full(), 3);
          else tma_load_mc(b + bx * 8192, &tm_w2, bx * 64, sl * 448 + (c - 7) * 64, r.full(), 3);
        }
        r.next();
      }
    }
  } else {
    asm volatile("setmaxnreg.inc.sync.aligned.u32 240;");
    pdl_wait();
    GT_MIN(8);
    const int warp = (tid >> 5) & 3;
    if (wg == 0) ffn_consumer<0>(r, sb, bar_a, rt, warp, lane, &tm_acc);
    else ffn_consumer<1>(r, sb, bar_a, rt, warp, lane, &tm_acc);
  }
  cluster_sync_all();
  GT_MAX(9);
}

__global__ void __launch_bounds__(512) mod_kernel(const __nv_bfloat16* __restrict__ c, const __nv_bfloat16* __restrict__ wm) {
  __shared__ float red[32][33];
  const int tid = threadIdx.x;
  pdl_launch();
  GT_MIN(0);
  if (blockIdx.x < 84) {
    const int cl = tid & 15, kg = tid >> 4;
    const int col = blockIdx.x * 32 + cl * 2;
    uint32_t v[14];
#pragma unroll
    for (int i = 0; i < 14; ++i) v[i] = *reinterpret_cast<const uint32_t*>(wm + (size_t)(kg * 14 + i) * (6 * DM) + col);
    float a0 = 0.f, a1 = 0.f;
#pragma unroll
    for (int i = 0; i < 14; ++i) {
      float cv = __bfloat162float(c[kg * 14 + i]);
      float sv = rbf(cv / (1.f + __expf(-cv)));
      a0 = fmaf(sv, bf_lo(v[i]), a0); a1 = fmaf(sv, bf_hi(v[i]), a1);
    }
    red[kg][cl * 2] = a0; red[kg][cl * 2 + 1] = a1;
    __syncthreads();
    if (tid < 32) {
      float s = 0.f;
#pragma unroll
      for (int i = 0; i < 32; ++i) s += red[i][tid];
      g_mod[blockIdx.x * 32 + tid] = rbf(s);
    }
  } else {
    float4 z = make_float4(0.f, 0.f, 0.f, 0.f);
    const int n4 = SEQ * DM / 4;
    for (int i = (blockIdx.x - 84) * 512 + tid; i < n4; i += (gridDim.x - 84) * 512) {
      reinterpret_cast<float4*>(g_acc1)[i] = z; reinterpret_cast<float4*>(g_acc2)[i] = z;
    }
  }
  if (blockIdx.x < 84) GT_MAX(1); else GT_MAX(13);
}

__device__ __forceinline__ void ln_row(const float (&x)[14], const float* __restrict__ shift, const float* __restrict__ scale,
                                       __nv_bfloat16* __restrict__ out, int lane) {
  float2 sc[7], sh[7];
#pragma unroll
  for (int i = 0; i < 7; ++i) {
    sc[i] = *reinterpret_cast<const float2*>(scale + i * 64 + lane * 2);
    sh[i] = *reinterpret_cast<const float2*>(shift + i * 64 + lane * 2);
  }
  float s = 0.f;
#pragma unroll
  for (int i = 0; i < 14; ++i) s += x[i];
#pragma unroll
  for (int o = 16; o; o >>= 1) s += __shfl_xor_sync(0xffffffffu, s, o);
  const float mean = s * (1.f / DM);
  float q = 0.f;
#pragma unroll
  for (int i = 0; i < 14; ++i) { float d = x[i] - mean; q = fmaf(d, d, q); }
#pragma unroll
  for (int o = 16; o; o >>= 1) q += __shfl_xor_sync(0xffffffffu, q, o);
  const float mb = rbf(mean), vb = rbf(q * (1.f / DM));
  const float den = rbf(sqrtf(rbf(vb + 1e-5f)));
#pragma unroll
  for (int i = 0; i < 7; ++i) {
    int col = i * 64 + lane * 2;
    float y0 = rbf(rbf(x[2 * i] - mb) / den), y1 = rbf(rbf(x[2 * i + 1] - mb) / den);
    y0 = rbf(y0 * rbf(1.f + sc[i].x)); y1 = rbf(y1 * rbf(1.f + sc[i].y));
    *reinterpret_cast<uint32_t*>(out + col) = pack_bf16(y0 + sh[i].x, y1 + sh[i].y);
  }
}

__global__ void __launch_bounds__(256) ln1_kernel(const __nv_bfloat16* __restrict__ x) {
  const int lane = threadIdx.x & 31, row = blockIdx.x * 8 + (threadIdx.x >> 5);
  float v[14];
#pragma unroll
  for (int i = 0; i < 7; ++i) {
    uint32_t u = *reinterpret_cast<const uint32_t*>(x + (size_t)row * DM + i * 64 + lane * 2);
    v[2 * i] = bf_lo(u); v[2 * i + 1] = bf_hi(u);
  }
  pdl_wait();
  GT_MIN(2);
  ln_row(v, g_mod + 0 * DM, g_mod + 1 * DM, g_h + (size_t)row * DM, lane);
  GT_MAX(3);
  pdl_launch();
}

__global__ void __launch_bounds__(256) ln2_kernel(const __nv_bfloat16* __restrict__ x) {
  const int lane = threadIdx.x & 31, row = blockIdx.x * 8 + (threadIdx.x >> 5);
  float v[14];
  uint32_t xu[7];
#pragma unroll
  for (int i = 0; i < 7; ++i) xu[i] = *reinterpret_cast<const uint32_t*>(x + (size_t)row * DM + i * 64 + lane * 2);
  pdl_wait();
  GT_MIN(6);
  float2 av[7], gv[7];
#pragma unroll
  for (int i = 0; i < 7; ++i) {
    av[i] = *reinterpret_cast<const float2*>(g_acc1 + (size_t)row * DM + i * 64 + lane * 2);
    gv[i] = *reinterpret_cast<const float2*>(g_mod + 2 * DM + i * 64 + lane * 2);
  }
#pragma unroll
  for (int i = 0; i < 7; ++i) {
    int col = i * 64 + lane * 2;
    uint32_t u = xu[i];
    float t0 = rbf(gv[i].x * rbf(av[i].x)), t1 = rbf(gv[i].y * rbf(av[i].y));
    v[2 * i] = rbf(bf_lo(u) + t0); v[2 * i + 1] = rbf(bf_hi(u) + t1);
    *reinterpret_cast<uint32_t*>(g_x1 + (size_t)row * DM + col) = pack_bf16(v[2 * i], v[2 * i + 1]);
  }
  ln_row(v, g_mod + 3 * DM, g_mod + 4 * DM, g_h2 + (size_t)row * DM, lane);
  GT_MAX(7);
  pdl_launch();
}

__global__ void __launch_bounds__(256) final_kernel(__nv_bfloat16* __restrict__ out) {
  const int i = blockIdx.x * 256 + threadIdx.x;
  const int col = (i * 4) % DM;
  pdl_wait();
  GT_MIN(10);
  float4 a = reinterpret_cast<const float4*>(g_acc2)[i];
  uint2 u = reinterpret_cast<const uint2*>(g_x1)[i];
  float4 gb = *reinterpret_cast<const float4*>(g_mod + 5 * DM + col);
  uint2 o;
  o.x = pack_bf16(bf_lo(u.x) + rbf(gb.x * rbf(a.x)), bf_hi(u.x) + rbf(gb.y * rbf(a.y)));
  o.y = pack_bf16(bf_lo(u.y) + rbf(gb.z * rbf(a.z)), bf_hi(u.y) + rbf(gb.w * rbf(a.w)));
  reinterpret_cast<uint2*>(out)[i] = o;
  GT_MAX(11);
}

typedef CUresult (*EncodeFn)(CUtensorMap*, CUtensorMapDataType, cuuint32_t, void*, const cuuint64_t*, const cuuint64_t*,
                             const cuuint32_t*, const cuuint32_t*, CUtensorMapInterleave, CUtensorMapSwizzle,
                             CUtensorMapL2promotion, CUtensorMapFloatOOBfill);

static CUtensorMap make_map(EncodeFn enc, const void* ptr, uint64_t cols, uint64_t rows, uint32_t bx, uint32_t by,
                            bool f32 = false) {
  CUtensorMap m;
  cuuint64_t dims[2] = {cols, rows};
  cuuint64_t strides[1] = {cols * (f32 ? 4 : 2)};
  cuuint32_t box[2] = {bx, by};
  cuuint32_t es[2] = {1, 1};
  enc(&m, f32 ? CU_TENSOR_MAP_DATA_TYPE_FLOAT32 : CU_TENSOR_MAP_DATA_TYPE_BFLOAT16, 2, const_cast<void*>(ptr), dims, strides, box, es, CU_TENSOR_MAP_INTERLEAVE_NONE,
      CU_TENSOR_MAP_SWIZZLE_128B, CU_TENSOR_MAP_L2_PROMOTION_L2_256B, CU_TENSOR_MAP_FLOAT_OOB_FILL_NONE);
  return m;
}

template <typename... Args>
static void launch(void (*k)(Args...), dim3 grid, dim3 block, size_t smem, bool pdl, Args... args) {
  cudaLaunchConfig_t cfg = {};
  cfg.gridDim = grid; cfg.blockDim = block; cfg.dynamicSmemBytes = smem; cfg.stream = cudaStreamPerThread;
  cudaLaunchAttribute at[1];
  at[0].id = cudaLaunchAttributeProgrammaticStreamSerialization; at[0].val.programmaticStreamSerializationAllowed = 1;
  cfg.attrs = at; cfg.numAttrs = pdl ? 1 : 0;
  cudaLaunchKernelEx(&cfg, k, args...);
}

extern "C" void kernel_launch(void* const* d_in, const int* in_sizes, int n_in, void* d_out, int out_size) {
  const __nv_bfloat16* x = (const __nv_bfloat16*)d_in[0];
  const void* kc = d_in[1]; const void* vc = d_in[2]; const void* wq = d_in[3]; const void* wo = d_in[4];
  const void* w1 = d_in[6]; const void* w2 = d_in[7];
  const __nv_bfloat16* c = (const __nv_bfloat16*)d_in[8];
  const __nv_bfloat16* wm = (const __nv_bfloat16*)d_in[9];

  void* fn = nullptr; cudaDriverEntryPointQueryResult qr;
  cudaGetDriverEntryPoint("cuTensorMapEncodeTiled", &fn, cudaEnableDefault, &qr);
  EncodeFn enc = (EncodeFn)fn;
  void *p_h, *p_oA, *p_h2, *p_a1, *p_a2;
  cudaGetSymbolAddress(&p_a1, g_acc1); cudaGetSymbolAddress(&p_a2, g_acc2);
  cudaGetSymbolAddress(&p_h, g_h); cudaGetSymbolAddress(&p_oA, g_oA); cudaGetSymbolAddress(&p_h2, g_h2);
  CUtensorMap tm_h = make_map(enc, p_h, DM, SEQ, 64, 128);
  CUtensorMap tm_wq = make_map(enc, wq, 4096, DM, 64, 64);
  CUtensorMap tm_k = make_map(enc, kc, DH, HKV * SKV, 64, 128);
  CUtensorMap tm_v = make_map(enc, vc, DH, HKV * SKV, 64, 64);
  CUtensorMap tm_wo = make_map(enc, wo, DM, 4096, 64, 64);
  CUtensorMap tm_oA = make_map(enc, p_oA, DH, HKV * SEQ, 64, 128);
  CUtensorMap tm_oAs = make_map(enc, p_oA, DH, HKV * SEQ, 64, 64);
  CUtensorMap tm_a1 = make_map(enc, p_a1, DM, SEQ, 32, 8, true), tm_a2 = make_map(enc, p_a2, DM, SEQ, 32, 8, true);
  CUtensorMap tm_h2 = make_map(enc, p_h2, DM, SEQ, 64, 64);
  CUtensorMap tm_w1 = make_map(enc, w1, DFF, DM, 64, 64);
  CUtensorMap tm_w2 = make_map(enc, w2, DM, DFF, 64, 64);
  cudaFuncSetAttribute(attn_kernel, cudaFuncAttributeMaxDynamicSharedMemorySize, SM_TOTAL);
  cudaFuncSetAttribute(ffn_kernel, cudaFuncAttributeMaxDynamicSharedMemorySize, F_TOTAL);

  launch(mod_kernel, dim3(84 + 90), dim3(512), 0, false, c, wm);
  launch(ln1_kernel, dim3(SEQ / 8), dim3(256), 0, true, x);
  launch(attn_kernel, dim3(16, 8), dim3(384), SM_TOTAL, true, tm_h, tm_wq, tm_k, tm_v, tm_wo, tm_oA, tm_oAs, tm_a1);
  launch(ln2_kernel, dim3(SEQ / 8), dim3(256), 0, true, x);
  launch(ffn_kernel, dim3(32, 4), dim3(384), F_TOTAL, true, tm_h2, tm_w1, tm_w2, tm_a2);
  launch(final_kernel, dim3(SEQ * DM / 1024), dim3(256), 0, true, (__nv_bfloat16*)d_out);
}
```

```cpp
#include <cuda_runtime.h>
#include <cuda_bf16.h>
#include <cuda.h>
#include <stdint.h>

constexpr int SEQ = 2048, DM = 448, HKV = 8, SKV = 2048, DH = 256, WIN = 512, DFF = 1792;

__device__ __align__(1024) float          g_mod[6 * DM];
__device__ __align__(1024) __nv_bfloat16  g_h[SEQ * DM];
__device__ __align__(1024) __nv_bfloat16  g_oA[HKV * SEQ * DH];
__device__ __align__(1024) float          g_acc1[SEQ * DM];
__device__ __align__(1024) float          g_acc2[SEQ * DM];
__device__ __align__(1024) __nv_bfloat16  g_x1[SEQ * DM];
__device__ __align__(1024) __nv_bfloat16  g_h2[SEQ * DM];

__device__ __forceinline__ uint32_t smem_u32(const void* p) { return (uint32_t)__cvta_generic_to_shared(p); }
__device__ __forceinline__ void mbar_init(uint32_t bar, uint32_t cnt) {
  asm volatile("mbarrier.init.shared::cta.b64 [%0], %1;" ::"r"(bar), "r"(cnt));
}
__device__ __forceinline__ void mbar_expect_tx(uint32_t bar, uint32_t bytes) {
  asm volatile("mbarrier.arrive.expect_tx.shared::cta.b64 _, [%0], %1;" ::"r"(bar), "r"(bytes) : "memory");
}
__device__ __forceinline__ void mbar_arrive(uint32_t bar) {
  asm volatile("mbarrier.arrive.shared::cta.b64 _, [%0];" ::"r"(bar) : "memory");
}
__device__ __forceinline__ void mbar_arrive_remote(uint32_t bar, uint32_t cta) {
  asm volatile("{\n.reg .b32 ra;\nmapa.shared::cluster.u32 ra, %0, %1;\n"
               "mbarrier.arrive.shared::cluster.b64 _, [ra];\n}\n" ::"r"(bar), "r"(cta) : "memory");
}
__device__ __forceinline__ void mbar_wait(uint32_t bar, uint32_t parity) {
  asm volatile("{\n.reg .pred p;\nLAB_WAIT:\n"
               "mbarrier.try_wait.parity.shared::cta.b64 p, [%0], %1, 0x989680;\n"
               "@p bra LAB_DONE;\nbra LAB_WAIT;\nLAB_DONE:\n}\n" ::"r"(bar), "r"(parity) : "memory");
}
__device__ __forceinline__ void mbar_wait_cluster(uint32_t bar, uint32_t parity) {
  asm volatile("{\n.reg .pred p;\nLAB_WAIT:\n"
               "mbarrier.try_wait.parity.acquire.cluster.shared::cta.b64 p, [%0], %1, 0x989680;\n"
               "@p bra LAB_DONE;\nbra LAB_WAIT;\nLAB_DONE:\n}\n" ::"r"(bar), "r"(parity) : "memory");
}
__device__ __forceinline__ void tma_load(uint32_t dst, const CUtensorMap* m, int c0, int c1, uint32_t bar) {
  asm volatile("cp.async.bulk.tensor.2d.shared::cluster.global.mbarrier::complete_tx::bytes [%0], [%1, {%3, %4}], [%2];"
               ::"r"(dst), "l"(m), "r"(bar), "r"(c0), "r"(c1) : "memory");
}
__device__ __forceinline__ void tma_load_mc(uint32_t dst, const CUtensorMap* m, int c0, int c1, uint32_t bar, uint16_t mask) {
  asm volatile("cp.async.bulk.tensor.2d.shared::cluster.global.mbarrier::complete_tx::bytes.multicast::cluster [%0], [%1, {%3, %4}], [%2], %5;"
               ::"r"(dst), "l"(m), "r"(bar), "r"(c0), "r"(c1), "h"(mask) : "memory");
}
__device__ __forceinline__ void cluster_sync_all() {
  asm volatile("barrier.cluster.arrive.release.aligned;\nbarrier.cluster.wait.acquire.aligned;\n" ::: "memory");
}
__device__ __forceinline__ uint32_t cluster_rank() { uint32_t r; asm volatile("mov.u32 %0, %%cluster_ctarank;" : "=r"(r)); return r; }
__device__ __forceinline__ void wg_fence() { asm volatile("wgmma.fence.sync.aligned;" ::: "memory"); }
__device__ __forceinline__ void wg_commit() { asm volatile("wgmma.commit_group.sync.aligned;" ::: "memory"); }
template <int N> __device__ __forceinline__ void wg_wait() { asm volatile("wgmma.wait_group.sync.aligned %0;" ::"n"(N) : "memory"); }
__device__ __forceinline__ void bar_sync(int id, int n) { asm volatile("bar.sync %0, %1;" ::"r"(id), "r"(n) : "memory"); }
__device__ __forceinline__ void bar_arrive(int id, int n) { asm volatile("bar.arrive %0, %1;" ::"r"(id), "r"(n) : "memory"); }
__device__ __forceinline__ void fence_async_smem() { asm volatile("fence.proxy.async.shared::cta;" ::: "memory"); }
__device__ __forceinline__ void fence_async() { asm volatile("fence.proxy.async;" ::: "memory"); }
__device__ __forceinline__ uint64_t mk_desc(uint32_t saddr, uint32_t lbo, uint32_t sbo) {
  return (uint64_t)((saddr & 0x3FFFF) >> 4) | ((uint64_t)(lbo >> 4) << 16) | ((uint64_t)(sbo >> 4) << 32) | (1ull << 62);
}
__device__ __forceinline__ uint32_t pack_bf16(float lo, float hi) {
  uint32_t r; asm("cvt.rn.bf16x2.f32 %0, %1, %2;" : "=r"(r) : "f"(hi), "f"(lo)); return r;
}
__device__ __forceinline__ float bf_lo(uint32_t v) { return __uint_as_float(v << 16); }
__device__ __forceinline__ float bf_hi(uint32_t v) { return __uint_as_float(v & 0xFFFF0000u); }
__device__ __forceinline__ float rbf(float x) { return __bfloat162float(__float2bfloat16_rn(x)); }
__device__ __forceinline__ float ex2(float x) { float r; asm("ex2.approx.ftz.f32 %0, %1;" : "=f"(r) : "f"(x)); return r; }
__device__ __forceinline__ void red_add_v2(float* p, float a, float b) {
  asm volatile("red.global.add.v2.f32 [%0], {%1, %2};" ::"l"(p), "f"(a), "f"(b) : "memory");
}
__device__ __forceinline__ void pdl_wait() { asm volatile("griddepcontrol.wait;" ::: "memory"); }
__device__ __forceinline__ void pdl_launch() { asm volatile("griddepcontrol.launch_dependents;" ::: "memory"); }

__device__ __forceinline__ void wgmma_m64n256k16_ss_tb(float (&d)[128], uint64_t da, uint64_t db, int sc) {
  asm volatile("{\n.reg .pred p;\nsetp.ne.b32 p, %130, 0;\n"
    "wgmma.mma_async.sync.aligned.m64n256k16.f32.bf16.bf16 {%0, %1, %2, %3, %4, %5, %6, %7, %8, %9, %10, %11, %12, %13, %14, %15, %16, %17, %18, %19, %20, %21, %22, %23, %24, %25, %26, %27, %28, %29, %30, %31, %32, %33, %34, %35, %36, %37, %38, %39, %40, %41, %42, %43, %44, %45, %46, %47, %48, %49, %50, %51, %52, %53, %54, %55, %56, %57, %58, %59, %60, %61, %62, %63, %64, %65, %66, %67, %68, %69, %70, %71, %72, %73, %74, %75, %76, %77, %78, %79, %80, %81, %82, %83, %84, %85, %86, %87, %88, %89, %90, %91, %92, %93, %94, %95, %96, %97, %98, %99, %100, %101, %102, %103, %104, %105, %106, %107, %108, %109, %110, %111, %112, %113, %114, %115, %116, %117, %118, %119, %120, %121, %122, %123, %124, %125, %126, %127}, %128, %129, p, 1, 1, 0, 1;\n}\n"
    : "+f"(d[0]), "+f"(d[1]), "+f"(d[2]), "+f"(d[3]), "+f"(d[4]), "+f"(d[5]), "+f"(d[6]), "+f"(d[7]), "+f"(d[8]), "+f"(d[9]), "+f"(d[10]), "+f"(d[11]), "+f"(d[12]), "+f"(d[13]), "+f"(d[14]), "+f"(d[15]), "+f"(d[16]), "+f"(d[17]), "+f"(d[18]), "+f"(d[19]), "+f"(d[20]), "+f"(d[21]), "+f"(d[22]), "+f"(d[23]), "+f"(d[24]), "+f"(d[25]), "+f"(d[26]), "+f"(d[27]), "+f"(d[28]), "+f"(d[29]), "+f"(d[30]), "+f"(d[31]), "+f"(d[32]), "+f"(d[33]), "+f"(d[34]), "+f"(d[35]), "+f"(d[36]), "+f"(d[37]), "+f"(d[38]), "+f"(d[39]), "+f"(d[40]), "+f"(d[41]), "+f"(d[42]), "+f"(d[43]), "+f"(d[44]), "+f"(d[45]), "+f"(d[46]), "+f"(d[47]), "+f"(d[48]), "+f"(d[49]), "+f"(d[50]), "+f"(d[51]), "+f"(d[52]), "+f"(d[53]), "+f"(d[54]), "+f"(d[55]), "+f"(d[56]), "+f"(d[57]), "+f"(d[58]), "+f"(d[59]), "+f"(d[60]), "+f"(d[61]), "+f"(d[62]), "+f"(d[63]), "+f"(d[64]), "+f"(d[65]), "+f"(d[66]), "+f"(d[67]), "+f"(d[68]), "+f"(d[69]), "+f"(d[70]), "+f"(d[71]), "+f"(d[72]), "+f"(d[73]), "+f"(d[74]), "+f"(d[75]), "+f"(d[76]), "+f"(d[77]), "+f"(d[78]), "+f"(d[79]), "+f"(d[80]), "+f"(d[81]), "+f"(d[82]), "+f"(d[83]), "+f"(d[84]), "+f"(d[85]), "+f"(d[86]), "+f"(d[87]), "+f"(d[88]), "+f"(d[89]), "+f"(d[90]), "+f"(d[91]), "+f"(d[92]), "+f"(d[93]), "+f"(d[94]), "+f"(d[95]), "+f"(d[96]), "+f"(d[97]), "+f"(d[98]), "+f"(d[99]), "+f"(d[100]), "+f"(d[101]), "+f"(d[102]), "+f"(d[103]), "+f"(d[104]), "+f"(d[105]), "+f"(d[106]), "+f"(d[107]), "+f"(d[108]), "+f"(d[109]), "+f"(d[110]), "+f"(d[111]), "+f"(d[112]), "+f"(d[113]), "+f"(d[114]), "+f"(d[115]), "+f"(d[116]), "+f"(d[117]), "+f"(d[118]), "+f"(d[119]), "+f"(d[120]), "+f"(d[121]), "+f"(d[122]), "+f"(d[123]), "+f"(d[124]), "+f"(d[125]), "+f"(d[126]), "+f"(d[127])
    : "l"(da), "l"(db), "r"(sc));
}
__device__ __forceinline__ void wgmma_m64n128k16_ss(float (&d)[64], uint64_t da, uint64_t db, int sc) {
  asm volatile("{\n.reg .pred p;\nsetp.ne.b32 p, %66, 0;\n"
    "wgmma.mma_async.sync.aligned.m64n128k16.f32.bf16.bf16 {%0, %1, %2, %3, %4, %5, %6, %7, %8, %9, %10, %11, %12, %13, %14, %15, %16, %17, %18, %19, %20, %21, %22, %23, %24, %25, %26, %27, %28, %29, %30, %31, %32, %33, %34, %35, %36, %37, %38, %39, %40, %41, %42, %43, %44, %45, %46, %47, %48, %49, %50, %51, %52, %53, %54, %55, %56, %57, %58, %59, %60, %61, %62, %63}, %64, %65, p, 1, 1, 0, 0;\n}\n"
    : "+f"(d[0]), "+f"(d[1]), "+f"(d[2]), "+f"(d[3]), "+f"(d[4]), "+f"(d[5]), "+f"(d[6]), "+f"(d[7]), "+f"(d[8]), "+f"(d[9]), "+f"(d[10]), "+f"(d[11]), "+f"(d[12]), "+f"(d[13]), "+f"(d[14]), "+f"(d[15]), "+f"(d[16]), "+f"(d[17]), "+f"(d[18]), "+f"(d[19]), "+f"(d[20]), "+f"(d[21]), "+f"(d[22]), "+f"(d[23]), "+f"(d[24]), "+f"(d[25]), "+f"(d[26]), "+f"(d[27]), "+f"(d[28]), "+f"(d[29]), "+f"(d[30]), "+f"(d[31]), "+f"(d[32]), "+f"(d[33]), "+f"(d[34]), "+f"(d[35]), "+f"(d[36]), "+f"(d[37]), "+f"(d[38]), "+f"(d[39]), "+f"(d[40]), "+f"(d[41]), "+f"(d[42]), "+f"(d[43]), "+f"(d[44]), "+f"(d[45]), "+f"(d[46]), "+f"(d[47]), "+f"(d[48]), "+f"(d[49]), "+f"(d[50]), "+f"(d[51]), "+f"(d[52]), "+f"(d[53]), "+f"(d[54]), "+f"(d[55]), "+f"(d[56]), "+f"(d[57]), "+f"(d[58]), "+f"(d[59]), "+f"(d[60]), "+f"(d[61]), "+f"(d[62]), "+f"(d[63])
    : "l"(da), "l"(db), "r"(sc));
}
__device__ __forceinline__ void wgmma_m64n256k16_rs_tb(float (&d)[128], uint32_t a0, uint32_t a1, uint32_t a2, uint32_t a3, uint64_t db, int sc) {
  asm volatile("{\n.reg .pred p;\nsetp.ne.b32 p, %133, 0;\n"
    "wgmma.mma_async.sync.aligned.m64n256k16.f32.bf16.bf16 {%0, %1, %2, %3, %4, %5, %6, %7, %8, %9, %10, %11, %12, %13, %14, %15, %16, %17, %18, %19, %20, %21, %22, %23, %24, %25, %26, %27, %28, %29, %30, %31, %32, %33, %34, %35, %36, %37, %38, %39, %40, %41, %42, %43, %44, %45, %46, %47, %48, %49, %50, %51, %52, %53, %54, %55, %56, %57, %58, %59, %60, %61, %62, %63, %64, %65, %66, %67, %68, %69, %70, %71, %72, %73, %74, %75, %76, %77, %78, %79, %80, %81, %82, %83, %84, %85, %86, %87, %88, %89, %90, %91, %92, %93, %94, %95, %96, %97, %98, %99, %100, %101, %102, %103, %104, %105, %106, %107, %108, %109, %110, %111, %112, %113, %114, %115, %116, %117, %118, %119, %120, %121, %122, %123, %124, %125, %126, %127}, {%128, %129, %130, %131}, %132, p, 1, 1, 1;\n}\n"
    : "+f"(d[0]), "+f"(d[1]), "+f"(d[2]), "+f"(d[3]), "+f"(d[4]), "+f"(d[5]), "+f"(d[6]), "+f"(d[7]), "+f"(d[8]), "+f"(d[9]), "+f"(d[10]), "+f"(d[11]), "+f"(d[12]), "+f"(d[13]), "+f"(d[14]), "+f"(d[15]), "+f"(d[16]), "+f"(d[17]), "+f"(d[18]), "+f"(d[19]), "+f"(d[20]), "+f"(d[21]), "+f"(d[22]), "+f"(d[23]), "+f"(d[24]), "+f"(d[25]), "+f"(d[26]), "+f"(d[27]), "+f"(d[28]), "+f"(d[29]), "+f"(d[30]), "+f"(d[31]), "+f"(d[32]), "+f"(d[33]), "+f"(d[34]), "+f"(d[35]), "+f"(d[36]), "+f"(d[37]), "+f"(d[38]), "+f"(d[39]), "+f"(d[40]), "+f"(d[41]), "+f"(d[42]), "+f"(d[43]), "+f"(d[44]), "+f"(d[45]), "+f"(d[46]), "+f"(d[47]), "+f"(d[48]), "+f"(d[49]), "+f"(d[50]), "+f"(d[51]), "+f"(d[52]), "+f"(d[53]), "+f"(d[54]), "+f"(d[55]), "+f"(d[56]), "+f"(d[57]), "+f"(d[58]), "+f"(d[59]), "+f"(d[60]), "+f"(d[61]), "+f"(d[62]), "+f"(d[63]), "+f"(d[64]), "+f"(d[65]), "+f"(d[66]), "+f"(d[67]), "+f"(d[68]), "+f"(d[69]), "+f"(d[70]), "+f"(d[71]), "+f"(d[72]), "+f"(d[73]), "+f"(d[74]), "+f"(d[75]), "+f"(d[76]), "+f"(d[77]), "+f"(d[78]), "+f"(d[79]), "+f"(d[80]), "+f"(d[81]), "+f"(d[82]), "+f"(d[83]), "+f"(d[84]), "+f"(d[85]), "+f"(d[86]), "+f"(d[87]), "+f"(d[88]), "+f"(d[89]), "+f"(d[90]), "+f"(d[91]), "+f"(d[92]), "+f"(d[93]), "+f"(d[94]), "+f"(d[95]), "+f"(d[96]), "+f"(d[97]), "+f"(d[98]), "+f"(d[99]), "+f"(d[100]), "+f"(d[101]), "+f"(d[102]), "+f"(d[103]), "+f"(d[104]), "+f"(d[105]), "+f"(d[106]), "+f"(d[107]), "+f"(d[108]), "+f"(d[109]), "+f"(d[110]), "+f"(d[111]), "+f"(d[112]), "+f"(d[113]), "+f"(d[114]), "+f"(d[115]), "+f"(d[116]), "+f"(d[117]), "+f"(d[118]), "+f"(d[119]), "+f"(d[120]), "+f"(d[121]), "+f"(d[122]), "+f"(d[123]), "+f"(d[124]), "+f"(d[125]), "+f"(d[126]), "+f"(d[127])
    : "r"(a0), "r"(a1), "r"(a2), "r"(a3), "l"(db), "r"(sc));
}
__device__ __forceinline__ void wgmma_m64n128k16_ss_tb(float (&d)[64], uint64_t da, uint64_t db, int sc) {
  asm volatile("{\n.reg .pred p;\nsetp.ne.b32 p, %66, 0;\n"
    "wgmma.mma_async.sync.aligned.m64n128k16.f32.bf16.bf16 {%0, %1, %2, %3, %4, %5, %6, %7, %8, %9, %10, %11, %12, %13, %14, %15, %16, %17, %18, %19, %20, %21, %22, %23, %24, %25, %26, %27, %28, %29, %30, %31, %32, %33, %34, %35, %36, %37, %38, %39, %40, %41, %42, %43, %44, %45, %46, %47, %48, %49, %50, %51, %52, %53, %54, %55, %56, %57, %58, %59, %60, %61, %62, %63}, %64, %65, p, 1, 1, 0, 1;\n}\n"
    : "+f"(d[0]), "+f"(d[1]), "+f"(d[2]), "+f"(d[3]), "+f"(d[4]), "+f"(d[5]), "+f"(d[6]), "+f"(d[7]), "+f"(d[8]), "+f"(d[9]), "+f"(d[10]), "+f"(d[11]), "+f"(d[12]), "+f"(d[13]), "+f"(d[14]), "+f"(d[15]), "+f"(d[16]), "+f"(d[17]), "+f"(d[18]), "+f"(d[19]), "+f"(d[20]), "+f"(d[21]), "+f"(d[22]), "+f"(d[23]), "+f"(d[24]), "+f"(d[25]), "+f"(d[26]), "+f"(d[27]), "+f"(d[28]), "+f"(d[29]), "+f"(d[30]), "+f"(d[31]), "+f"(d[32]), "+f"(d[33]), "+f"(d[34]), "+f"(d[35]), "+f"(d[36]), "+f"(d[37]), "+f"(d[38]), "+f"(d[39]), "+f"(d[40]), "+f"(d[41]), "+f"(d[42]), "+f"(d[43]), "+f"(d[44]), "+f"(d[45]), "+f"(d[46]), "+f"(d[47]), "+f"(d[48]), "+f"(d[49]), "+f"(d[50]), "+f"(d[51]), "+f"(d[52]), "+f"(d[53]), "+f"(d[54]), "+f"(d[55]), "+f"(d[56]), "+f"(d[57]), "+f"(d[58]), "+f"(d[59]), "+f"(d[60]), "+f"(d[61]), "+f"(d[62]), "+f"(d[63])
    : "l"(da), "l"(db), "r"(sc));
}
__device__ __forceinline__ void wgmma_m64n128k16_rs_tb(float (&d)[64], uint32_t a0, uint32_t a1, uint32_t a2, uint32_t a3, uint64_t db, int sc) {
  asm volatile("{\n.reg .pred p;\nsetp.ne.b32 p, %69, 0;\n"
    "wgmma.mma_async.sync.aligned.m64n128k16.f32.bf16.bf16 {%0, %1, %2, %3, %4, %5, %6, %7, %8, %9, %10, %11, %12, %13, %14, %15, %16, %17, %18, %19, %20, %21, %22, %23, %24, %25, %26, %27, %28, %29, %30, %31, %32, %33, %34, %35, %36, %37, %38, %39, %40, %41, %42, %43, %44, %45, %46, %47, %48, %49, %50, %51, %52, %53, %54, %55, %56, %57, %58, %59, %60, %61, %62, %63}, {%64, %65, %66, %67}, %68, p, 1, 1, 1;\n}\n"
    : "+f"(d[0]), "+f"(d[1]), "+f"(d[2]), "+f"(d[3]), "+f"(d[4]), "+f"(d[5]), "+f"(d[6]), "+f"(d[7]), "+f"(d[8]), "+f"(d[9]), "+f"(d[10]), "+f"(d[11]), "+f"(d[12]), "+f"(d[13]), "+f"(d[14]), "+f"(d[15]), "+f"(d[16]), "+f"(d[17]), "+f"(d[18]), "+f"(d[19]), "+f"(d[20]), "+f"(d[21]), "+f"(d[22]), "+f"(d[23]), "+f"(d[24]), "+f"(d[25]), "+f"(d[26]), "+f"(d[27]), "+f"(d[28]), "+f"(d[29]), "+f"(d[30]), "+f"(d[31]), "+f"(d[32]), "+f"(d[33]), "+f"(d[34]), "+f"(d[35]), "+f"(d[36]), "+f"(d[37]), "+f"(d[38]), "+f"(d[39]), "+f"(d[40]), "+f"(d[41]), "+f"(d[42]), "+f"(d[43]), "+f"(d[44]), "+f"(d[45]), "+f"(d[46]), "+f"(d[47]), "+f"(d[48]), "+f"(d[49]), "+f"(d[50]), "+f"(d[51]), "+f"(d[52]), "+f"(d[53]), "+f"(d[54]), "+f"(d[55]), "+f"(d[56]), "+f"(d[57]), "+f"(d[58]), "+f"(d[59]), "+f"(d[60]), "+f"(d[61]), "+f"(d[62]), "+f"(d[63])
    : "r"(a0), "r"(a1), "r"(a2), "r"(a3), "l"(db), "r"(sc));
}
__device__ __forceinline__ void wgmma_m64n64k16_ss_tb(float (&d)[32], uint64_t da, uint64_t db, int sc) {
  asm volatile("{\n.reg .pred p;\nsetp.ne.b32 p, %34, 0;\n"
    "wgmma.mma_async.sync.aligned.m64n64k16.f32.bf16.bf16 {%0, %1, %2, %3, %4, %5, %6, %7, %8, %9, %10, %11, %12, %13, %14, %15, %16, %17, %18, %19, %20, %21, %22, %23, %24, %25, %26, %27, %28, %29, %30, %31}, %32, %33, p, 1, 1, 0, 1;\n}\n"
    : "+f"(d[0]), "+f"(d[1]), "+f"(d[2]), "+f"(d[3]), "+f"(d[4]), "+f"(d[5]), "+f"(d[6]), "+f"(d[7]), "+f"(d[8]), "+f"(d[9]), "+f"(d[10]), "+f"(d[11]), "+f"(d[12]), "+f"(d[13]), "+f"(d[14]), "+f"(d[15]), "+f"(d[16]), "+f"(d[17]), "+f"(d[18]), "+f"(d[19]), "+f"(d[20]), "+f"(d[21]), "+f"(d[22]), "+f"(d[23]), "+f"(d[24]), "+f"(d[25]), "+f"(d[26]), "+f"(d[27]), "+f"(d[28]), "+f"(d[29]), "+f"(d[30]), "+f"(d[31])
    : "l"(da), "l"(db), "r"(sc));
}
__device__ __forceinline__ void wgmma_m64n64k16_rs_tb(float (&d)[32], uint32_t a0, uint32_t a1, uint32_t a2, uint32_t a3, uint64_t db, int sc) {
  asm volatile("{\n.reg .pred p;\nsetp.ne.b32 p, %37, 0;\n"
    "wgmma.mma_async.sync.aligned.m64n64k16.f32.bf16.bf16 {%0, %1, %2, %3, %4, %5, %6, %7, %8, %9, %10, %11, %12, %13, %14, %15, %16, %17, %18, %19, %20, %21, %22, %23, %24, %25, %26, %27, %28, %29, %30, %31}, {%32, %33, %34, %35}, %36, p, 1, 1, 1;\n}\n"
    : "+f"(d[0]), "+f"(d[1]), "+f"(d[2]), "+f"(d[3]), "+f"(d[4]), "+f"(d[5]), "+f"(d[6]), "+f"(d[7]), "+f"(d[8]), "+f"(d[9]), "+f"(d[10]), "+f"(d[11]), "+f"(d[12]), "+f"(d[13]), "+f"(d[14]), "+f"(d[15]), "+f"(d[16]), "+f"(d[17]), "+f"(d[18]), "+f"(d[19]), "+f"(d[20]), "+f"(d[21]), "+f"(d[22]), "+f"(d[23]), "+f"(d[24]), "+f"(d[25]), "+f"(d[26]), "+f"(d[27]), "+f"(d[28]), "+f"(d[29]), "+f"(d[30]), "+f"(d[31])
    : "r"(a0), "r"(a1), "r"(a2), "r"(a3), "l"(db), "r"(sc));
}
__device__ __forceinline__ void wgmma_m64n192k16_ss_tb(float (&d)[128], uint64_t da, uint64_t db, int sc) {
  asm volatile("{\n.reg .pred p;\nsetp.ne.b32 p, %98, 0;\n"
    "wgmma.mma_async.sync.aligned.m64n192k16.f32.bf16.bf16 {%0, %1, %2, %3, %4, %5, %6, %7, %8, %9, %10, %11, %12, %13, %14, %15, %16, %17, %18, %19, %20, %21, %22, %23, %24, %25, %26, %27, %28, %29, %30, %31, %32, %33, %34, %35, %36, %37, %38, %39, %40, %41, %42, %43, %44, %45, %46, %47, %48, %49, %50, %51, %52, %53, %54, %55, %56, %57, %58, %59, %60, %61, %62, %63, %64, %65, %66, %67, %68, %69, %70, %71, %72, %73, %74, %75, %76, %77, %78, %79, %80, %81, %82, %83, %84, %85, %86, %87, %88, %89, %90, %91, %92, %93, %94, %95}, %96, %97, p, 1, 1, 0, 1;\n}\n"
    : "+f"(d[0]), "+f"(d[1]), "+f"(d[2]), "+f"(d[3]), "+f"(d[4]), "+f"(d[5]), "+f"(d[6]), "+f"(d[7]), "+f"(d[8]), "+f"(d[9]), "+f"(d[10]), "+f"(d[11]), "+f"(d[12]), "+f"(d[13]), "+f"(d[14]), "+f"(d[15]), "+f"(d[16]), "+f"(d[17]), "+f"(d[18]), "+f"(d[19]), "+f"(d[20]), "+f"(d[21]), "+f"(d[22]), "+f"(d[23]), "+f"(d[24]), "+f"(d[25]), "+f"(d[26]), "+f"(d[27]), "+f"(d[28]), "+f"(d[29]), "+f"(d[30]), "+f"(d[31]), "+f"(d[32]), "+f"(d[33]), "+f"(d[34]), "+f"(d[35]), "+f"(d[36]), "+f"(d[37]), "+f"(d[38]), "+f"(d[39]), "+f"(d[40]), "+f"(d[41]), "+f"(d[42]), "+f"(d[43]), "+f"(d[44]), "+f"(d[45]), "+f"(d[46]), "+f"(d[47]), "+f"(d[48]), "+f"(d[49]), "+f"(d[50]), "+f"(d[51]), "+f"(d[52]), "+f"(d[53]), "+f"(d[54]), "+f"(d[55]), "+f"(d[56]), "+f"(d[57]), "+f"(d[58]), "+f"(d[59]), "+f"(d[60]), "+f"(d[61]), "+f"(d[62]), "+f"(d[63]), "+f"(d[64]), "+f"(d[65]), "+f"(d[66]), "+f"(d[67]), "+f"(d[68]), "+f"(d[69]), "+f"(d[70]), "+f"(d[71]), "+f"(d[72]), "+f"(d[73]), "+f"(d[74]), "+f"(d[75]), "+f"(d[76]), "+f"(d[77]), "+f"(d[78]), "+f"(d[79]), "+f"(d[80]), "+f"(d[81]), "+f"(d[82]), "+f"(d[83]), "+f"(d[84]), "+f"(d[85]), "+f"(d[86]), "+f"(d[87]), "+f"(d[88]), "+f"(d[89]), "+f"(d[90]), "+f"(d[91]), "+f"(d[92]), "+f"(d[93]), "+f"(d[94]), "+f"(d[95])
    : "l"(da), "l"(db), "r"(sc));
}

#define TM(id)
#define GT_MIN(i)
#define GT_MAX(i)

constexpr int NS = 5;
constexpr uint32_t STG = 32768;
constexpr uint32_t SM_Q = 0;
constexpr uint32_t SM_RING = 65536;
constexpr uint32_t SM_BAR = SM_RING + NS * STG;
constexpr uint32_t SM_TOTAL = SM_BAR + 256 + 1024;

struct Ring {
  uint32_t base, full0, empty0, st, ph, nst, stg;
  __device__ __forceinline__ void init(uint32_t sb) { base = sb + SM_RING; full0 = sb + SM_BAR; empty0 = sb + SM_BAR + 64; st = 0; ph = 0; nst = NS; stg = STG; }
  __device__ __forceinline__ uint32_t phase() const { return (ph >> st) & 1; }
  __device__ __forceinline__ uint32_t buf() const { return base + st * stg; }
  __device__ __forceinline__ uint32_t full() const { return full0 + st * 8; }
  __device__ __forceinline__ uint32_t empty() const { return empty0 + st * 8; }
  __device__ __forceinline__ void next() { ph ^= 1u << st; st = (st + 1 >= nst) ? 0 : st + 1; }
  __device__ __forceinline__ void shrink() { nst = NS - 1; if (st >= nst) st = 0; }
  __device__ __forceinline__ uint32_t acquire(uint32_t bytes) {
    mbar_wait(empty(), phase() ^ 1); mbar_expect_tx(full(), bytes); return buf();
  }
  __device__ __forceinline__ uint32_t wait() { mbar_wait(full(), phase()); return buf(); }
};
template <int CL = 2>
__device__ __forceinline__ void ring_release(uint32_t empty_bar, int lane) {
  __syncwarp();
  if (lane < CL) mbar_arrive_remote(empty_bar, (uint32_t)lane);
}

template <int CL>
__device__ __forceinline__ void gemm_k448_n256(Ring& r, float (&acc)[128], int wg, int lane) {
  uint32_t hb = 0, hrel = 0, prel = 0, phrel = 0;
#pragma unroll
  for (int c = 0; c < 7; ++c) {
    if ((c & 1) == 0) { hb = r.wait(); hrel = r.empty(); r.next(); }
    uint32_t wb = r.wait(); uint32_t wrel = r.empty(); r.next();
    uint64_t da = mk_desc(hb + (c & 1) * 16384 + wg * 8192, 16, 1024);
    uint64_t db = mk_desc(wb, 8192, 1024);
    wg_fence();
#pragma unroll
    for (int k = 0; k < 4; ++k) wgmma_m64n256k16_ss_tb(acc, da + k * 2, db + k * 128, (c | k) != 0);
    wg_commit();
    if (c > 0) {
      wg_wait<1>();
      ring_release<CL>(prel, lane);
      if ((c & 1) == 0) ring_release<CL>(phrel, lane);
    }
    prel = wrel; phrel = hrel;
  }
  wg_wait<0>();
  ring_release<CL>(prel, lane); ring_release<CL>(phrel, lane);
}

template <bool RELU>
__device__ __forceinline__ void store_tile_bf16(uint32_t base, const float (&acc)[128], int rloc, int t4) {
  uint32_t row0 = base + rloc * 128, row1 = row0 + 8 * 128;
  uint32_t sw = (uint32_t)(rloc & 7);
#pragma unroll
  for (int j = 0; j < 32; ++j) {
    uint32_t off = (uint32_t)(j >> 3) * 16384 + ((((uint32_t)j & 7) ^ sw) << 4) + t4 * 4;
    float a = acc[4 * j], b = acc[4 * j + 1], c = acc[4 * j + 2], d = acc[4 * j + 3];
    if (RELU) { a = fmaxf(a, 0.f); b = fmaxf(b, 0.f); c = fmaxf(c, 0.f); d = fmaxf(d, 0.f); }
    asm volatile("st.shared.b32 [%0], %1;" ::"r"(row0 + off), "r"(pack_bf16(a, b)) : "memory");
    asm volatile("st.shared.b32 [%0], %1;" ::"r"(row1 + off), "r"(pack_bf16(c, d)) : "memory");
  }
}

template <int NJ, int OFF = 0, int SZ = 64, bool WAIT = true>
__device__ __forceinline__ void red_rows(uint32_t stg, const CUtensorMap* tm, int row0, int col0, const float (&a)[SZ], int sel, int lane) {
  asm volatile("" : "+r"(stg), "+r"(lane));
  if (WAIT) {
    if (lane == 0) asm volatile("cp.async.bulk.wait_group.read 0;" ::: "memory");
    __syncwarp();
  }
  const uint32_t g = lane >> 2, t4 = lane & 3;
  const uint32_t wbase = stg + g * 128 + (t4 & 1) * 8;
#pragma unroll
  for (int j = 0; j < NJ; ++j)
    asm volatile("st.shared.v2.f32 [%0], {%1, %2};" ::"r"(wbase + (j >> 2) * 1024 + ((((j & 3) * 2 + (t4 >> 1)) ^ g) << 4)),
                 "f"(a[OFF + 4 * j + sel]), "f"(a[OFF + 4 * j + sel + 1]) : "memory");
  fence_async_smem();
  __syncwarp();
  if (lane == 0) {
#pragma unroll
    for (int b = 0; b < NJ / 4; ++b)
      asm volatile("cp.reduce.async.bulk.tensor.2d.global.shared::cta.add.tile.bulk_group [%0, {%2, %3}], [%1];"
                   ::"l"(tm), "r"(stg + b * 1024), "r"(col0 + b * 32), "r"(row0) : "memory");
    asm volatile("cp.async.bulk.commit_group;" ::: "memory");
  }
}

template <int NSM, int NRG, int CL>
__device__ __forceinline__ void out_proj(Ring& r, const uint32_t (&ob)[64], uint32_t abase,
                                         const CUtensorMap* tm, int roww, uint32_t stg, int lane) {
  constexpr int NST = (NSM + NRG) / 2;
  uint32_t prel = 0;
  float accA[64], accB[64];
  float(&cur32)[32] = *reinterpret_cast<float(*)[32]>(&accB[0]);
#pragma unroll
  for (int pass = 0; pass < 4; ++pass) {
    float(&cur)[64] = (pass & 1) ? accB : accA;
    float(&prv)[64] = (pass & 1) ? accA : accB;
#pragma unroll
    for (int st = 0; st < NST; ++st) {
      uint32_t wb = r.wait(); uint32_t rel = r.empty(); r.next();
      asm volatile("" : "+r"(abase));
      wg_fence();
#pragma unroll
      for (int cc = 0; cc < 2; ++cc) {
        const int c = 2 * st + cc;
#pragma unroll
        for (int k = 0; k < 4; ++k) {
          const int sc = (c | k) != 0;
          if (pass < 3) {
            uint64_t db = mk_desc(wb + cc * 16384 + k * 2048, 8192, 1024);
            if (c < NSM) wgmma_m64n128k16_ss_tb(cur, mk_desc(abase + c * 16384 + k * 32, 16, 1024), db, sc);
            else { const int o = (c - NSM) * 16 + 4 * k; wgmma_m64n128k16_rs_tb(cur, ob[o], ob[o + 1], ob[o + 2], ob[o + 3], db, sc); }
          } else {
            uint64_t db = mk_desc(wb + cc * 8192 + k * 2048, 8192, 1024);
            if (c < NSM) wgmma_m64n64k16_ss_tb(cur32, mk_desc(abase + c * 16384 + k * 32, 16, 1024), db, sc);
            else { const int o = (c - NSM) * 16 + 4 * k; wgmma_m64n64k16_rs_tb(cur32, ob[o], ob[o + 1], ob[o + 2], ob[o + 3], db, sc); }
          }
        }
      }
      wg_commit();
      if (pass | st) { wg_wait<1>(); ring_release<CL>(prel, lane); }
      prel = rel;
      if (pass > 0) {
        if (st == 0) red_rows<16>(stg, tm, roww, (pass - 1) * 128, prv, 0, lane);
        if (st == NST / 2) red_rows<16>(stg, tm, roww + 8, (pass - 1) * 128, prv, 2, lane);
      }
    }
  }
  wg_wait<0>(); ring_release<CL>(prel, lane);
  red_rows<8>(stg, tm, roww, 384, accB, 0, lane);
  red_rows<8>(stg, tm, roww + 8, 384, accB, 2, lane);
  if (lane == 0) asm volatile("cp.async.bulk.wait_group 0;" ::: "memory");
}
template <int CL>
__device__ __forceinline__ void out_proj_loads(Ring& r, const CUtensorMap* tm, int krow0, int nch, uint32_t rank) {
  r.shrink();
  constexpr uint16_t MASK = (1 << CL) - 1;
  for (int pass = 0; pass < 4; ++pass)
    for (int st = 0; st < nch / 2; ++st) {
      if (pass < 3) {
        uint32_t b = r.acquire(32768);
        for (int x = 0; x < 4 / CL; ++x) {
          const int bx = rank * (4 / CL) + x;
          tma_load_mc(b + bx * 8192, tm, pass * 128 + (bx & 1) * 64, krow0 + (2 * st + (bx >> 1)) * 64, r.full(), MASK);
        }
      } else {
        uint32_t b = r.acquire(16384);
        if (CL == 1) { for (int x = 0; x < 2; ++x) tma_load_mc(b + x * 8192, tm, 384, krow0 + (2 * st + x) * 64, r.full(), MASK); }
        else if (rank < 2) tma_load_mc(b + rank * 8192, tm, 384, krow0 + (2 * st + rank) * 64, r.full(), MASK);
      }
      r.next();
    }
}

#define ACL 2
__global__ void __cluster_dims__(ACL, 1, 1) __launch_bounds__(384, 1)
attn_kernel(const __grid_constant__ CUtensorMap tm_h, const __grid_constant__ CUtensorMap tm_wq,
            const __grid_constant__ CUtensorMap tm_k, const __grid_constant__ CUtensorMap tm_v,
            const __grid_constant__ CUtensorMap tm_wo, const __grid_constant__ CUtensorMap tm_oA,
            const __grid_constant__ CUtensorMap tm_oAs, const __grid_constant__ CUtensorMap tm_acc) {
  extern __shared__ uint8_t smem_raw[];
  const uint32_t sb = (smem_u32(smem_raw) + 1023) & ~1023u;
  const int tid = threadIdx.x, wg = tid >> 7, lane = tid & 31;
  const int qt = blockIdx.x, kvh = blockIdx.y;
  const uint32_t rank = cluster_rank();
  Ring r; r.init(sb);
  const uint32_t bar_oA = sb + SM_BAR + 128, bar_oAf = sb + SM_BAR + 136;
  if (tid == 0) {
    for (int i = 0; i < NS; ++i) { mbar_init(r.full0 + 8 * i, 1); mbar_init(r.empty0 + 8 * i, 8 * ACL); }
    mbar_init(bar_oA, 256); mbar_init(bar_oAf, 1);
    asm volatile("fence.mbarrier_init.release.cluster;" ::: "memory");
  }
  cluster_sync_all();
  pdl_wait();
  GT_MIN(4);

  if (wg == 2) {
    asm volatile("setmaxnreg.dec.sync.aligned.u32 24;");
    if (tid == 256) {
      const int krow0 = kvh * SKV + (SKV - WIN);
      for (int hh = 0; hh < 2; ++hh) {
        const int head = kvh * 2 + hh;
        for (int p = 0; p < 4; ++p) {
          int nc = (p < 3) ? 2 : 1;
          uint32_t b = r.acquire(nc * 16384);
          for (int c = 0; c < nc; ++c) tma_load(b + c * 16384, &tm_h, (2 * p + c) * 64, qt * 128, r.full());
          r.next();
          for (int c = 0; c < nc; ++c) {
            b = r.acquire(32768);
            for (int x = 0; x < 4 / ACL; ++x) {
              int bx = rank * 2 + x;
              tma_load_mc(b + bx * 8192, &tm_wq, head * 256 + bx * 64, (2 * p + c) * 64, r.full(), (1 << ACL) - 1);
            }
            r.next();
          }
        }
        for (int t = 0; t < 4; ++t) {
          for (int hf = 0; hf < 2; ++hf) {
            uint32_t b = r.acquire(32768);
            for (int x = 0; x < 2 / ACL; ++x)
              tma_load_mc(b + (rank + x) * 16384, &tm_k, (2 * hf + rank + x) * 64, krow0 + t * 128, r.full(), (1 << ACL) - 1);
            r.next();
          }
          for (int hf = 0; hf < 2; ++hf) {
            uint32_t b = r.acquire(32768);
            for (int x = 0; x < 4 / ACL; ++x) {
              int bx = rank * 2 + x;
              tma_load_mc(b + bx * 8192, &tm_v, bx * 64, krow0 + t * 128 + hf * 64, r.full(), (1 << ACL) - 1);
            }
            r.next();
          }
        }
      }
      mbar_wait(bar_oA, 0);
      mbar_expect_tx(bar_oAf, 65536);
      for (int c = 0; c < 4; ++c) tma_load(sb + SM_Q + c * 16384, &tm_oA, c * 64, kvh * SEQ + qt * 128, bar_oAf);
      out_proj_loads<ACL>(r, &tm_wo, kvh * 512, 8, rank);
    }
  } else {
    asm volatile("setmaxnreg.inc.sync.aligned.u32 240;");
    const int warp = (tid >> 5) & 3, g = lane >> 2, t4 = lane & 3;
    const int rloc = wg * 64 + warp * 16 + g;
    uint32_t ob[64];
    float acc[128];
    const float CS = 1.4426950408889634f * 0.0625f;
    TM(0);
#pragma unroll 1
    for (int hh = 0; hh < 2; ++hh) {
      gemm_k448_n256<ACL>(r, acc, wg, lane);
      TM(1);
      if (hh == 1) {
        if ((tid & 127) == 0) asm volatile("cp.async.bulk.wait_group.read 0;" ::: "memory");
        bar_sync(1 + wg, 128);
      }
      store_tile_bf16<false>(sb + SM_Q, acc, rloc, t4);
      fence_async_smem();
      bar_sync(1 + wg, 128);
      float m0 = -INFINITY, m1 = -INFINITY, l0 = 0.f, l1 = 0.f;
      const uint32_t qa0 = sb + SM_Q + wg * 8192;
      if (wg == 1) bar_arrive(3, 256);
      TM(2);
      bar_sync(3 + wg, 256);
#pragma unroll 1
      for (int t = 0; t < 4; ++t) {
        float s[64];
        TM(3);
        {
          uint32_t qa = qa0; asm volatile("" : "+r"(qa));
          uint32_t ka = r.wait(); uint32_t rel0 = r.empty(); r.next();
          wg_fence();
#pragma unroll
          for (int k = 0; k < 8; ++k)
            wgmma_m64n128k16_ss(s, mk_desc(qa + (k >> 2) * 16384 + (k & 3) * 32, 16, 1024),
                                mk_desc(ka + (k >> 2) * 16384 + (k & 3) * 32, 16, 1024), k != 0);
          wg_commit();
          uint32_t kb = r.wait(); uint32_t rel1 = r.empty(); r.next();
          wg_fence();
#pragma unroll
          for (int k = 0; k < 8; ++k)
            wgmma_m64n128k16_ss(s, mk_desc(qa + (2 + (k >> 2)) * 16384 + (k & 3) * 32, 16, 1024),
                                mk_desc(kb + (k >> 2) * 16384 + (k & 3) * 32, 16, 1024), 1);
          wg_commit();
          bar_arrive(4 - wg, 256);
          wg_wait<1>(); ring_release<ACL>(rel0, lane);
          wg_wait<0>(); ring_release<ACL>(rel1, lane);
        }
        TM(4);
        float mx0 = m0, mx1 = m1;
#pragma unroll
        for (int j = 0; j < 16; ++j) {
          uint32_t a = pack_bf16(s[4 * j], s[4 * j + 1]), b = pack_bf16(s[4 * j + 2], s[4 * j + 3]);
          s[4 * j] = bf_lo(a); s[4 * j + 1] = bf_hi(a); s[4 * j + 2] = bf_lo(b); s[4 * j + 3] = bf_hi(b);
          mx0 = fmaxf(mx0, fmaxf(s[4 * j], s[4 * j + 1])); mx1 = fmaxf(mx1, fmaxf(s[4 * j + 2], s[4 * j + 3]));
        }
        mx0 = fmaxf(mx0, __shfl_xor_sync(0xffffffffu, mx0, 1)); mx0 = fmaxf(mx0, __shfl_xor_sync(0xffffffffu, mx0, 2));
        mx1 = fmaxf(mx1, __shfl_xor_sync(0xffffffffu, mx1, 1)); mx1 = fmaxf(mx1, __shfl_xor_sync(0xffffffffu, mx1, 2));
        const float c0 = ex2((m0 - mx0) * CS), c1 = ex2((m1 - mx1) * CS);
        m0 = mx0; m1 = mx1;
        const float nb0 = -mx0 * CS, nb1 = -mx1 * CS;
        float ps0 = 0.f, ps1 = 0.f;
        uint32_t pa[32];
#pragma unroll
        for (int j = 0; j < 16; ++j) {
          float e0 = ex2(fmaf(s[4 * j], CS, nb0)), e1 = ex2(fmaf(s[4 * j + 1], CS, nb0));
          float e2 = ex2(fmaf(s[4 * j + 2], CS, nb1)), e3 = ex2(fmaf(s[4 * j + 3], CS, nb1));
          ps0 += e0 + e1; ps1 += e2 + e3;
          pa[2 * j] = pack_bf16(e0, e1); pa[2 * j + 1] = pack_bf16(e2, e3);
        }
        l0 = l0 * c0 + ps0; l1 = l1 * c1 + ps1;
        if (t > 0) {
#pragma unroll
          for (int j = 0; j < 32; ++j) { acc[4 * j] *= c0; acc[4 * j + 1] *= c0; acc[4 * j + 2] *= c1; acc[4 * j + 3] *= c1; }
        }
#pragma unroll
        for (int j = 0; j < 32; ++j) asm volatile("" : "+r"(pa[j]));
#pragma unroll
        for (int j = 0; j < 128; ++j) asm volatile("" : "+f"(acc[j]));
        asm volatile("" : "+f"(l0), "+f"(l1));
        TM(5);
        bar_sync(3 + wg, 256);
        TM(6);
        {
          uint32_t va = r.wait(); uint32_t rel0 = r.empty(); r.next();
          wg_fence();
#pragma unroll
          for (int k = 0; k < 4; ++k)
            wgmma_m64n256k16_rs_tb(acc, pa[4 * k], pa[4 * k + 1], pa[4 * k + 2], pa[4 * k + 3],
                                   mk_desc(va + k * 2048, 8192, 1024), (t | k) != 0);
          wg_commit();
          uint32_t vb = r.wait(); uint32_t rel1 = r.empty(); r.next();
          wg_fence();
#pragma unroll
          for (int k = 0; k < 4; ++k)
            wgmma_m64n256k16_rs_tb(acc, pa[16 + 4 * k], pa[16 + 4 * k + 1], pa[16 + 4 * k + 2], pa[16 + 4 * k + 3],
                                   mk_desc(vb + k * 2048, 8192, 1024), 1);
          wg_commit();
          if (t == 3 && wg == 0) bar_arrive(4, 256);
          wg_wait<1>(); ring_release<ACL>(rel0, lane);
          wg_wait<0>(); ring_release<ACL>(rel1, lane);
        }
      }
      TM(7);
      l0 += __shfl_xor_sync(0xffffffffu, l0, 1); l0 += __shfl_xor_sync(0xffffffffu, l0, 2);
      l1 += __shfl_xor_sync(0xffffffffu, l1, 1); l1 += __shfl_xor_sync(0xffffffffu, l1, 2);
      const float i0 = 1.f / l0, i1 = 1.f / l1;
#pragma unroll
      for (int j = 0; j < 32; ++j) {
        ob[2 * j] = pack_bf16(acc[4 * j] * i0, acc[4 * j + 1] * i0);
        ob[2 * j + 1] = pack_bf16(acc[4 * j + 2] * i1, acc[4 * j + 3] * i1);
      }
      if (hh == 0) {
        uint32_t row0 = sb + SM_Q + rloc * 128, row1 = row0 + 8 * 128;
        uint32_t sw = (uint32_t)(rloc & 7);
#pragma unroll
        for (int j = 0; j < 32; ++j) {
          uint32_t off = (uint32_t)(j >> 3) * 16384 + ((((uint32_t)j & 7) ^ sw) << 4) + t4 * 4;
          asm volatile("st.shared.b32 [%0], %1;" ::"r"(row0 + off), "r"(ob[2 * j]) : "memory");
          asm volatile("st.shared.b32 [%0], %1;" ::"r"(row1 + off), "r"(ob[2 * j + 1]) : "memory");
        }
        fence_async_smem();
        bar_sync(1 + wg, 128);
        if ((tid & 127) == 0) {
          for (int c = 0; c < 4; ++c)
            asm volatile("cp.async.bulk.tensor.2d.global.shared::cta.bulk_group [%0, {%2, %3}], [%1];"
                         ::"l"(&tm_oAs), "r"(sb + SM_Q + c * 16384 + wg * 8192), "r"(c * 64), "r"(kvh * SEQ + qt * 128 + wg * 64) : "memory");
          asm volatile("cp.async.bulk.commit_group;" ::: "memory");
        }
      }
    }
    if ((tid & 127) == 0) asm volatile("cp.async.bulk.wait_group 0;" ::: "memory");
    mbar_arrive(bar_oA);
    mbar_wait(bar_oAf, 0);
    TM(8);
    r.shrink();
    out_proj<4, 4, ACL>(r, ob, sb + SM_Q + wg * 8192, &tm_acc, qt * 128 + wg * 64 + warp * 16,
                   sb + SM_RING + (NS - 1) * STG + (wg * 4 + warp) * 4096, lane);
    TM(9);
  }
  cluster_sync_all();
  GT_MAX(5);
}

constexpr uint32_t F_STG = 57344, F_A = 0, F_RING = 57344, F_BAR = F_RING + 3 * F_STG, F_TOTAL = F_BAR + 256 + 1024;

template <int WG>
__device__ __forceinline__ void ffn_gemm(Ring& r, float (&acc)[128], uint32_t abase, int lane) {
  uint32_t prel = 0;
#pragma unroll
  for (int c = 0; c < 7; ++c) {
    uint32_t wb = r.wait(); uint32_t wrel = r.empty(); r.next();
    uint64_t da = mk_desc(abase + c * 8192, 16, 1024);
    uint64_t db = mk_desc(wb + WG * 32768, 8192, 1024);
    wg_fence();
#pragma unroll
    for (int k = 0; k < 4; ++k) {
      if (WG == 0) wgmma_m64n256k16_ss_tb(acc, da + k * 2, db + k * 128, (c | k) != 0);
      else wgmma_m64n192k16_ss_tb(acc, da + k * 2, db + k * 128, (c | k) != 0);
    }
    wg_commit();
    if (c > 0) { wg_wait<1>(); ring_release<2>(prel, lane); }
    prel = wrel;
  }
  wg_wait<0>();
  ring_release<2>(prel, lane);
}

template <int WG>
__device__ __forceinline__ void ffn_consumer(Ring& r, uint32_t sb, uint32_t bar_a, int rt, int warp, int lane, const CUtensorMap* tm) {
  const int g = lane >> 2, t4 = lane & 3, row = warp * 16 + g;
  float acc[128];
  TM(20);
  mbar_wait(bar_a, 0);
  TM(21);
  ffn_gemm<WG>(r, acc, sb + F_A, lane);
  TM(22);
  bar_sync(5, 256);
  {
    uint32_t row0 = sb + F_A + WG * 32768 + row * 128, row1 = row0 + 8 * 128;
    uint32_t sw = (uint32_t)(row & 7);
#pragma unroll
    for (int j = 0; j < (WG == 0 ? 32 : 24); ++j) {
      uint32_t off = (uint32_t)(j >> 3) * 8192 + ((((uint32_t)j & 7) ^ sw) << 4) + t4 * 4;
      asm volatile("st.shared.b32 [%0], %1;" ::"r"(row0 + off), "r"(pack_bf16(fmaxf(acc[4 * j], 0.f), fmaxf(acc[4 * j + 1], 0.f))) : "memory");
      asm volatile("st.shared.b32 [%0], %1;" ::"r"(row1 + off), "r"(pack_bf16(fmaxf(acc[4 * j + 2], 0.f), fmaxf(acc[4 * j + 3], 0.f))) : "memory");
    }
  }
  fence_async_smem();
  bar_sync(5, 256);
  TM(23);
  {
    float(&accA)[64] = *reinterpret_cast<float(*)[64]>(&acc[0]);
    float(&accB)[64] = *reinterpret_cast<float(*)[64]>(&acc[64]);
    float(&accB32)[32] = *reinterpret_cast<float(*)[32]>(&acc[64]);
    const int wi = WG * 4 + warp;
    const uint32_t stg = sb + F_RING + (wi / 3) * F_STG + 32768 + (wi % 3) * 8192;
    const int r0 = rt * 64 + warp * 16, c0 = WG * 256;
    uint32_t prel = 0;
#pragma unroll
    for (int pass = 0; pass < 2; ++pass) {
#pragma unroll
      for (int c = 0; c < 7; ++c) {
        uint32_t wb = r.wait(); uint32_t wrel = r.empty(); r.next();
        uint64_t da = mk_desc(sb + F_A + c * 8192, 16, 1024);
        uint64_t db = mk_desc(wb + WG * 16384, 8192, 1024);
        wg_fence();
#pragma unroll
        for (int k = 0; k < 4; ++k) {
          if (pass == 0) wgmma_m64n128k16_ss_tb(accA, da + k * 2, db + k * 128, (c | k) != 0);
          else if (WG == 0) wgmma_m64n128k16_ss_tb(accB, da + k * 2, db + k * 128, (c | k) != 0);
          else wgmma_m64n64k16_ss_tb(accB32, da + k * 2, db + k * 128, (c | k) != 0);
        }
        wg_commit();
        if (pass | c) { wg_wait<1>(); ring_release<2>(prel, lane); }
        prel = wrel;
        if (pass == 1 && c == 0) red_rows<16, 0, 64, false>(stg, tm, r0, c0, accA, 0, lane);
        if (pass == 1 && c == 2) red_rows<16, 0, 64, false>(stg + 4096, tm, r0 + 8, c0, accA, 2, lane);
      }
    }
    wg_wait<0>();
    ring_release<2>(prel, lane);
    TM(24);
    if (WG == 0) {
      red_rows<16, 0, 64, true>(stg, tm, r0, c0 + 128, accB, 0, lane);
      red_rows<16, 0, 64, false>(stg + 4096, tm, r0 + 8, c0 + 128, accB, 2, lane);
    } else {
      red_rows<8, 0, 64, true>(stg, tm, r0, c0 + 128, accB, 0, lane);
      red_rows<8, 0, 64, false>(stg + 4096, tm, r0 + 8, c0 + 128, accB, 2, lane);
    }
    if (lane == 0) asm volatile("cp.async.bulk.wait_group 0;" ::: "memory");
  }
  TM(25);
}

__global__ void __cluster_dims__(2, 1, 1) __launch_bounds__(384, 1)
ffn_kernel(const __grid_constant__ CUtensorMap tm_h2, const __grid_constant__ CUtensorMap tm_w1,
           const __grid_constant__ CUtensorMap tm_w2, const __grid_constant__ CUtensorMap tm_acc) {
  extern __shared__ uint8_t smem_raw[];
  const uint32_t sb = (smem_u32(smem_raw) + 1023) & ~1023u;
  const int tid = threadIdx.x, wg = tid >> 7, lane = tid & 31;
  const int rt = blockIdx.x, sl = blockIdx.y;
  const uint32_t rank = cluster_rank();
  Ring r; r.base = sb + F_RING; r.full0 = sb + F_BAR; r.empty0 = sb + F_BAR + 64; r.st = 0; r.ph = 0; r.nst = 3; r.stg = F_STG;
  const uint32_t bar_a = sb + F_BAR + 128;
  if (tid == 0) {
    for (int i = 0; i < 3; ++i) { mbar_init(r.full0 + 8 * i, 1); mbar_init(r.empty0 + 8 * i, 16); }
    mbar_init(bar_a, 1);
    asm volatile("fence.mbarrier_init.release.cluster;" ::: "memory");
  }
  cluster_sync_all();
  if (wg == 2) {
    asm volatile("setmaxnreg.dec.sync.aligned.u32 24;");
    if (tid == 256) {
      const int b0 = rank ? 4 : 0, b1 = rank ? 7 : 4;
      pdl_wait();
      mbar_expect_tx(bar_a, 57344);
      for (int k = 0; k < 7; ++k) tma_load(sb + F_A + k * 8192, &tm_h2, k * 64, rt * 64, bar_a);
      for (int c = 0; c < 7; ++c) {
        uint32_t b = r.acquire(F_STG);
        for (int bx = b0; bx < b1; ++bx) tma_load_mc(b + bx * 8192, &tm_w1, sl * 448 + bx * 64, c * 64, r.full(), 3);
        r.next();
      }
      for (int c = 0; c < 14; ++c) {
        const int pass = c / 7, kr = sl * 448 + (c % 7) * 64;
        uint32_t b = r.acquire(pass ? 24576 : 32768);
        for (int x = 0; x < 2; ++x) {
          const int slot = rank * 2 + x;
          if (pass && slot == 3) continue;
          const int bx = (slot >> 1) * 4 + pass * 2 + (slot & 1);
          tma_load_mc(b + slot * 8192, &tm_w2, bx * 64, kr, r.full(), 3);
        }
        r.next();
      }
    }
  } else {
    asm volatile("setmaxnreg.inc.sync.aligned.u32 240;");
    pdl_wait();
    GT_MIN(8);
    const int warp = (tid >> 5) & 3;
    if (wg == 0) ffn_consumer<0>(r, sb, bar_a, rt, warp, lane, &tm_acc);
    else ffn_consumer<1>(r, sb, bar_a, rt, warp, lane, &tm_acc);
  }
  cluster_sync_all();
  GT_MAX(9);
}

__global__ void __launch_bounds__(512) mod_kernel(const __nv_bfloat16* __restrict__ c, const __nv_bfloat16* __restrict__ wm) {
  __shared__ float red[32][33];
  const int tid = threadIdx.x;
  pdl_launch();
  GT_MIN(0);
  if (blockIdx.x < 84) {
    const int cl = tid & 15, kg = tid >> 4;
    const int col = blockIdx.x * 32 + cl * 2;
    uint32_t v[14];
#pragma unroll
    for (int i = 0; i < 14; ++i) v[i] = *reinterpret_cast<const uint32_t*>(wm + (size_t)(kg * 14 + i) * (6 * DM) + col);
    float a0 = 0.f, a1 = 0.f;
#pragma unroll
    for (int i = 0; i < 14; ++i) {
      float cv = __bfloat162float(c[kg * 14 + i]);
      float sv = rbf(cv / (1.f + __expf(-cv)));
      a0 = fmaf(sv, bf_lo(v[i]), a0); a1 = fmaf(sv, bf_hi(v[i]), a1);
    }
    red[kg][cl * 2] = a0; red[kg][cl * 2 + 1] = a1;
    __syncthreads();
    if (tid < 32) {
      float s = 0.f;
#pragma unroll
      for (int i = 0; i < 32; ++i) s += red[i][tid];
      g_mod[blockIdx.x * 32 + tid] = rbf(s);
    }
  } else {
    float4 z = make_float4(0.f, 0.f, 0.f, 0.f);
    const int n4 = SEQ * DM / 4;
    for (int i = (blockIdx.x - 84) * 512 + tid; i < n4; i += (gridDim.x - 84) * 512) {
      reinterpret_cast<float4*>(g_acc1)[i] = z; reinterpret_cast<float4*>(g_acc2)[i] = z;
    }
  }
  if (blockIdx.x < 84) GT_MAX(1); else GT_MAX(13);
}

__device__ __forceinline__ void ln_row(const float (&x)[14], const float* __restrict__ shift, const float* __restrict__ scale,
                                       __nv_bfloat16* __restrict__ out, int lane) {
  float2 sc[7], sh[7];
#pragma unroll
  for (int i = 0; i < 7; ++i) {
    sc[i] = *reinterpret_cast<const float2*>(scale + i * 64 + lane * 2);
    sh[i] = *reinterpret_cast<const float2*>(shift + i * 64 + lane * 2);
  }
  float s = 0.f;
#pragma unroll
  for (int i = 0; i < 14; ++i) s += x[i];
#pragma unroll
  for (int o = 16; o; o >>= 1) s += __shfl_xor_sync(0xffffffffu, s, o);
  const float mean = s * (1.f / DM);
  float q = 0.f;
#pragma unroll
  for (int i = 0; i < 14; ++i) { float d = x[i] - mean; q = fmaf(d, d, q); }
#pragma unroll
  for (int o = 16; o; o >>= 1) q += __shfl_xor_sync(0xffffffffu, q, o);
  const float mb = rbf(mean), vb = rbf(q * (1.f / DM));
  const float den = rbf(sqrtf(rbf(vb + 1e-5f)));
#pragma unroll
  for (int i = 0; i < 7; ++i) {
    int col = i * 64 + lane * 2;
    float y0 = rbf(rbf(x[2 * i] - mb) / den), y1 = rbf(rbf(x[2 * i + 1] - mb) / den);
    y0 = rbf(y0 * rbf(1.f + sc[i].x)); y1 = rbf(y1 * rbf(1.f + sc[i].y));
    *reinterpret_cast<uint32_t*>(out + col) = pack_bf16(y0 + sh[i].x, y1 + sh[i].y);
  }
}

__global__ void __launch_bounds__(256) ln1_kernel(const __nv_bfloat16* __restrict__ x) {
  const int lane = threadIdx.x & 31, row = blockIdx.x * 8 + (threadIdx.x >> 5);
  float v[14];
#pragma unroll
  for (int i = 0; i < 7; ++i) {
    uint32_t u = *reinterpret_cast<const uint32_t*>(x + (size_t)row * DM + i * 64 + lane * 2);
    v[2 * i] = bf_lo(u); v[2 * i + 1] = bf_hi(u);
  }
  pdl_wait();
  GT_MIN(2);
  ln_row(v, g_mod + 0 * DM, g_mod + 1 * DM, g_h + (size_t)row * DM, lane);
  GT_MAX(3);
  pdl_launch();
}

__global__ void __launch_bounds__(256) ln2_kernel(const __nv_bfloat16* __restrict__ x) {
  const int lane = threadIdx.x & 31, row = blockIdx.x * 8 + (threadIdx.x >> 5);
  float v[14];
  uint32_t xu[7];
#pragma unroll
  for (int i = 0; i < 7; ++i) xu[i] = *reinterpret_cast<const uint32_t*>(x + (size_t)row * DM + i * 64 + lane * 2);
  pdl_wait();
  GT_MIN(6);
  float2 av[7], gv[7];
#pragma unroll
  for (int i = 0; i < 7; ++i) {
    av[i] = *reinterpret_cast<const float2*>(g_acc1 + (size_t)row * DM + i * 64 + lane * 2);
    gv[i] = *reinterpret_cast<const float2*>(g_mod + 2 * DM + i * 64 + lane * 2);
  }
#pragma unroll
  for (int i = 0; i < 7; ++i) {
    int col = i * 64 + lane * 2;
    uint32_t u = xu[i];
    float t0 = rbf(gv[i].x * rbf(av[i].x)), t1 = rbf(gv[i].y * rbf(av[i].y));
    v[2 * i] = rbf(bf_lo(u) + t0); v[2 * i + 1] = rbf(bf_hi(u) + t1);
    *reinterpret_cast<uint32_t*>(g_x1 + (size_t)row * DM + col) = pack_bf16(v[2 * i], v[2 * i + 1]);
  }
  ln_row(v, g_mod + 3 * DM, g_mod + 4 * DM, g_h2 + (size_t)row * DM, lane);
  GT_MAX(7);
  pdl_launch();
}

__global__ void __launch_bounds__(256) final_kernel(__nv_bfloat16* __restrict__ out) {
  const int i = blockIdx.x * 256 + threadIdx.x;
  const int col = (i * 4) % DM;
  pdl_wait();
  GT_MIN(10);
  float4 a = reinterpret_cast<const float4*>(g_acc2)[i];
  uint2 u = reinterpret_cast<const uint2*>(g_x1)[i];
  float4 gb = *reinterpret_cast<const float4*>(g_mod + 5 * DM + col);
  uint2 o;
  o.x = pack_bf16(bf_lo(u.x) + rbf(gb.x * rbf(a.x)), bf_hi(u.x) + rbf(gb.y * rbf(a.y)));
  o.y = pack_bf16(bf_lo(u.y) + rbf(gb.z * rbf(a.z)), bf_hi(u.y) + rbf(gb.w * rbf(a.w)));
  reinterpret_cast<uint2*>(out)[i] = o;
  GT_MAX(11);
}

typedef CUresult (*EncodeFn)(CUtensorMap*, CUtensorMapDataType, cuuint32_t, void*, const cuuint64_t*, const cuuint64_t*,
                             const cuuint32_t*, const cuuint32_t*, CUtensorMapInterleave, CUtensorMapSwizzle,
                             CUtensorMapL2promotion, CUtensorMapFloatOOBfill);

static CUtensorMap make_map(EncodeFn enc, const void* ptr, uint64_t cols, uint64_t rows, uint32_t bx, uint32_t by,
                            bool f32 = false) {
  CUtensorMap m;
  cuuint64_t dims[2] = {cols, rows};
  cuuint64_t strides[1] = {cols * (f32 ? 4 : 2)};
  cuuint32_t box[2] = {bx, by};
  cuuint32_t es[2] = {1, 1};
  enc(&m, f32 ? CU_TENSOR_MAP_DATA_TYPE_FLOAT32 : CU_TENSOR_MAP_DATA_TYPE_BFLOAT16, 2, const_cast<void*>(ptr), dims, strides, box, es, CU_TENSOR_MAP_INTERLEAVE_NONE,
      CU_TENSOR_MAP_SWIZZLE_128B, CU_TENSOR_MAP_L2_PROMOTION_L2_256B, CU_TENSOR_MAP_FLOAT_OOB_FILL_NONE);
  return m;
}

template <typename... Args>
static void launch(void (*k)(Args...), dim3 grid, dim3 block, size_t smem, bool pdl, Args... args) {
  cudaLaunchConfig_t cfg = {};
  cfg.gridDim = grid; cfg.blockDim = block; cfg.dynamicSmemBytes = smem; cfg.stream = cudaStreamPerThread;
  cudaLaunchAttribute at[1];
  at[0].id = cudaLaunchAttributeProgrammaticStreamSerialization; at[0].val.programmaticStreamSerializationAllowed = 1;
  cfg.attrs = at; cfg.numAttrs = pdl ? 1 : 0;
  cudaLaunchKernelEx(&cfg, k, args...);
}

extern "C" void kernel_launch(void* const* d_in, const int* in_sizes, int n_in, void* d_out, int out_size) {
  const __nv_bfloat16* x = (const __nv_bfloat16*)d_in[0];
  const void* kc = d_in[1]; const void* vc = d_in[2]; const void* wq = d_in[3]; const void* wo = d_in[4];
  const void* w1 = d_in[6]; const void* w2 = d_in[7];
  const __nv_bfloat16* c = (const __nv_bfloat16*)d_in[8];
  const __nv_bfloat16* wm = (const __nv_bfloat16*)d_in[9];

  void* fn = nullptr; cudaDriverEntryPointQueryResult qr;
  cudaGetDriverEntryPoint("cuTensorMapEncodeTiled", &fn, cudaEnableDefault, &qr);
  EncodeFn enc = (EncodeFn)fn;
  void *p_h, *p_oA, *p_h2, *p_a1, *p_a2;
  cudaGetSymbolAddress(&p_a1, g_acc1); cudaGetSymbolAddress(&p_a2, g_acc2);
  cudaGetSymbolAddress(&p_h, g_h); cudaGetSymbolAddress(&p_oA, g_oA); cudaGetSymbolAddress(&p_h2, g_h2);
  CUtensorMap tm_h = make_map(enc, p_h, DM, SEQ, 64, 128);
  CUtensorMap tm_wq = make_map(enc, wq, 4096, DM, 64, 64);
  CUtensorMap tm_k = make_map(enc, kc, DH, HKV * SKV, 64, 128);
  CUtensorMap tm_v = make_map(enc, vc, DH, HKV * SKV, 64, 64);
  CUtensorMap tm_wo = make_map(enc, wo, DM, 4096, 64, 64);
  CUtensorMap tm_oA = make_map(enc, p_oA, DH, HKV * SEQ, 64, 128);
  CUtensorMap tm_oAs = make_map(enc, p_oA, DH, HKV * SEQ, 64, 64);
  CUtensorMap tm_a1 = make_map(enc, p_a1, DM, SEQ, 32, 8, true), tm_a2 = make_map(enc, p_a2, DM, SEQ, 32, 8, true);
  CUtensorMap tm_h2 = make_map(enc, p_h2, DM, SEQ, 64, 64);
  CUtensorMap tm_w1 = make_map(enc, w1, DFF, DM, 64, 64);
  CUtensorMap tm_w2 = make_map(enc, w2, DM, DFF, 64, 64);
  cudaFuncSetAttribute(attn_kernel, cudaFuncAttributeMaxDynamicSharedMemorySize, SM_TOTAL);
  cudaFuncSetAttribute(ffn_kernel, cudaFuncAttributeMaxDynamicSharedMemorySize, F_TOTAL);

  launch(mod_kernel, dim3(84 + 90), dim3(512), 0, false, c, wm);
  launch(ln1_kernel, dim3(SEQ / 8), dim3(256), 0, true, x);
  launch(attn_kernel, dim3(16, 8), dim3(384), SM_TOTAL, true, tm_h, tm_wq, tm_k, tm_v, tm_wo, tm_oA, tm_oAs, tm_a1);
  launch(ln2_kernel, dim3(SEQ / 8), dim3(256), 0, true, x);
  launch(ffn_kernel, dim3(32, 4), dim3(384), F_TOTAL, true, tm_h2, tm_w1, tm_w2, tm_a2);
  launch(final_kernel, dim3(SEQ * DM / 1024), dim3(256), 0, true, (__nv_bfloat16*)d_out);
}
```

```cpp
#include <cuda_runtime.h>
#include <cuda_bf16.h>
#include <cuda.h>
#include <stdint.h>

constexpr int SEQ = 2048, DM = 448, HKV = 8, SKV = 2048, DH = 256, WIN = 512, DFF = 1792;

__device__ __align__(1024) float          g_mod[6 * DM];
__device__ __align__(1024) __nv_bfloat16  g_h[SEQ * DM];
__device__ __align__(1024) __nv_bfloat16  g_oA[HKV * SEQ * DH];
__device__ __align__(1024) float          g_acc1[SEQ * DM];
__device__ __align__(1024) float          g_acc2[SEQ * DM];
__device__ __align__(1024) __nv_bfloat16  g_x1[SEQ * DM];
__device__ __align__(1024) __nv_bfloat16  g_h2[SEQ * DM];

__device__ __forceinline__ uint32_t smem_u32(const void* p) { return (uint32_t)__cvta_generic_to_shared(p); }
__device__ __forceinline__ void mbar_init(uint32_t bar, uint32_t cnt) {
  asm volatile("mbarrier.init.shared::cta.b64 [%0], %1;" ::"r"(bar), "r"(cnt));
}
__device__ __forceinline__ void mbar_expect_tx(uint32_t bar, uint32_t bytes) {
  asm volatile("mbarrier.arrive.expect_tx.shared::cta.b64 _, [%0], %1;" ::"r"(bar), "r"(bytes) : "memory");
}
__device__ __forceinline__ void mbar_arrive(uint32_t bar) {
  asm volatile("mbarrier.arrive.shared::cta.b64 _, [%0];" ::"r"(bar) : "memory");
}
__device__ __forceinline__ void mbar_arrive_remote(uint32_t bar, uint32_t cta) {
  asm volatile("{\n.reg .b32 ra;\nmapa.shared::cluster.u32 ra, %0, %1;\n"
               "mbarrier.arrive.shared::cluster.b64 _, [ra];\n}\n" ::"r"(bar), "r"(cta) : "memory");
}
__device__ __forceinline__ void mbar_wait(uint32_t bar, uint32_t parity) {
  asm volatile("{\n.reg .pred p;\nLAB_WAIT:\n"
               "mbarrier.try_wait.parity.shared::cta.b64 p, [%0], %1, 0x989680;\n"
               "@p bra LAB_DONE;\nbra LAB_WAIT;\nLAB_DONE:\n}\n" ::"r"(bar), "r"(parity) : "memory");
}
__device__ __forceinline__ void mbar_wait_cluster(uint32_t bar, uint32_t parity) {
  asm volatile("{\n.reg .pred p;\nLAB_WAIT:\n"
               "mbarrier.try_wait.parity.acquire.cluster.shared::cta.b64 p, [%0], %1, 0x989680;\n"
               "@p bra LAB_DONE;\nbra LAB_WAIT;\nLAB_DONE:\n}\n" ::"r"(bar), "r"(parity) : "memory");
}
__device__ __forceinline__ void tma_load(uint32_t dst, const CUtensorMap* m, int c0, int c1, uint32_t bar) {
  asm volatile("cp.async.bulk.tensor.2d.shared::cluster.global.mbarrier::complete_tx::bytes [%0], [%1, {%3, %4}], [%2];"
               ::"r"(dst), "l"(m), "r"(bar), "r"(c0), "r"(c1) : "memory");
}
__device__ __forceinline__ void tma_load_mc(uint32_t dst, const CUtensorMap* m, int c0, int c1, uint32_t bar, uint16_t mask) {
  asm volatile("cp.async.bulk.tensor.2d.shared::cluster.global.mbarrier::complete_tx::bytes.multicast::cluster [%0], [%1, {%3, %4}], [%2], %5;"
               ::"r"(dst), "l"(m), "r"(bar), "r"(c0), "r"(c1), "h"(mask) : "memory");
}
__device__ __forceinline__ void cluster_sync_all() {
  asm volatile("barrier.cluster.arrive.release.aligned;\nbarrier.cluster.wait.acquire.aligned;\n" ::: "memory");
}
__device__ __forceinline__ uint32_t cluster_rank() { uint32_t r; asm volatile("mov.u32 %0, %%cluster_ctarank;" : "=r"(r)); return r; }
__device__ __forceinline__ void wg_fence() { asm volatile("wgmma.fence.sync.aligned;" ::: "memory"); }
__device__ __forceinline__ void wg_commit() { asm volatile("wgmma.commit_group.sync.aligned;" ::: "memory"); }
template <int N> __device__ __forceinline__ void wg_wait() { asm volatile("wgmma.wait_group.sync.aligned %0;" ::"n"(N) : "memory"); }
__device__ __forceinline__ void bar_sync(int id, int n) { asm volatile("bar.sync %0, %1;" ::"r"(id), "r"(n) : "memory"); }
__device__ __forceinline__ void bar_arrive(int id, int n) { asm volatile("bar.arrive %0, %1;" ::"r"(id), "r"(n) : "memory"); }
__device__ __forceinline__ void fence_async_smem() { asm volatile("fence.proxy.async.shared::cta;" ::: "memory"); }
__device__ __forceinline__ void fence_async() { asm volatile("fence.proxy.async;" ::: "memory"); }
__device__ __forceinline__ uint64_t mk_desc(uint32_t saddr, uint32_t lbo, uint32_t sbo) {
  return (uint64_t)((saddr & 0x3FFFF) >> 4) | ((uint64_t)(lbo >> 4) << 16) | ((uint64_t)(sbo >> 4) << 32) | (1ull << 62);
}
__device__ __forceinline__ uint32_t pack_bf16(float lo, float hi) {
  uint32_t r; asm("cvt.rn.bf16x2.f32 %0, %1, %2;" : "=r"(r) : "f"(hi), "f"(lo)); return r;
}
__device__ __forceinline__ float bf_lo(uint32_t v) { return __uint_as_float(v << 16); }
__device__ __forceinline__ float bf_hi(uint32_t v) { return __uint_as_float(v & 0xFFFF0000u); }
__device__ __forceinline__ float rbf(float x) { return __bfloat162float(__float2bfloat16_rn(x)); }
__device__ __forceinline__ float ex2(float x) { float r; asm("ex2.approx.ftz.f32 %0, %1;" : "=f"(r) : "f"(x)); return r; }
__device__ __forceinline__ void red_add_v2(float* p, float a, float b) {
  asm volatile("red.global.add.v2.f32 [%0], {%1, %2};" ::"l"(p), "f"(a), "f"(b) : "memory");
}
__device__ __forceinline__ void pdl_wait() { asm volatile("griddepcontrol.wait;" ::: "memory"); }
__device__ __forceinline__ void pdl_launch() { asm volatile("griddepcontrol.launch_dependents;" ::: "memory"); }

__device__ __forceinline__ void wgmma_m64n256k16_ss_tb(float (&d)[128], uint64_t da, uint64_t db, int sc) {
  asm volatile("{\n.reg .pred p;\nsetp.ne.b32 p, %130, 0;\n"
    "wgmma.mma_async.sync.aligned.m64n256k16.f32.bf16.bf16 {%0, %1, %2, %3, %4, %5, %6, %7, %8, %9, %10, %11, %12, %13, %14, %15, %16, %17, %18, %19, %20, %21, %22, %23, %24, %25, %26, %27, %28, %29, %30, %31, %32, %33, %34, %35, %36, %37, %38, %39, %40, %41, %42, %43, %44, %45, %46, %47, %48, %49, %50, %51, %52, %53, %54, %55, %56, %57, %58, %59, %60, %61, %62, %63, %64, %65, %66, %67, %68, %69, %70, %71, %72, %73, %74, %75, %76, %77, %78, %79, %80, %81, %82, %83, %84, %85, %86, %87, %88, %89, %90, %91, %92, %93, %94, %95, %96, %97, %98, %99, %100, %101, %102, %103, %104, %105, %106, %107, %108, %109, %110, %111, %112, %113, %114, %115, %116, %117, %118, %119, %120, %121, %122, %123, %124, %125, %126, %127}, %128, %129, p, 1, 1, 0, 1;\n}\n"
    : "+f"(d[0]), "+f"(d[1]), "+f"(d[2]), "+f"(d[3]), "+f"(d[4]), "+f"(d[5]), "+f"(d[6]), "+f"(d[7]), "+f"(d[8]), "+f"(d[9]), "+f"(d[10]), "+f"(d[11]), "+f"(d[12]), "+f"(d[13]), "+f"(d[14]), "+f"(d[15]), "+f"(d[16]), "+f"(d[17]), "+f"(d[18]), "+f"(d[19]), "+f"(d[20]), "+f"(d[21]), "+f"(d[22]), "+f"(d[23]), "+f"(d[24]), "+f"(d[25]), "+f"(d[26]), "+f"(d[27]), "+f"(d[28]), "+f"(d[29]), "+f"(d[30]), "+f"(d[31]), "+f"(d[32]), "+f"(d[33]), "+f"(d[34]), "+f"(d[35]), "+f"(d[36]), "+f"(d[37]), "+f"(d[38]), "+f"(d[39]), "+f"(d[40]), "+f"(d[41]), "+f"(d[42]), "+f"(d[43]), "+f"(d[44]), "+f"(d[45]), "+f"(d[46]), "+f"(d[47]), "+f"(d[48]), "+f"(d[49]), "+f"(d[50]), "+f"(d[51]), "+f"(d[52]), "+f"(d[53]), "+f"(d[54]), "+f"(d[55]), "+f"(d[56]), "+f"(d[57]), "+f"(d[58]), "+f"(d[59]), "+f"(d[60]), "+f"(d[61]), "+f"(d[62]), "+f"(d[63]), "+f"(d[64]), "+f"(d[65]), "+f"(d[66]), "+f"(d[67]), "+f"(d[68]), "+f"(d[69]), "+f"(d[70]), "+f"(d[71]), "+f"(d[72]), "+f"(d[73]), "+f"(d[74]), "+f"(d[75]), "+f"(d[76]), "+f"(d[77]), "+f"(d[78]), "+f"(d[79]), "+f"(d[80]), "+f"(d[81]), "+f"(d[82]), "+f"(d[83]), "+f"(d[84]), "+f"(d[85]), "+f"(d[86]), "+f"(d[87]), "+f"(d[88]), "+f"(d[89]), "+f"(d[90]), "+f"(d[91]), "+f"(d[92]), "+f"(d[93]), "+f"(d[94]), "+f"(d[95]), "+f"(d[96]), "+f"(d[97]), "+f"(d[98]), "+f"(d[99]), "+f"(d[100]), "+f"(d[101]), "+f"(d[102]), "+f"(d[103]), "+f"(d[104]), "+f"(d[105]), "+f"(d[106]), "+f"(d[107]), "+f"(d[108]), "+f"(d[109]), "+f"(d[110]), "+f"(d[111]), "+f"(d[112]), "+f"(d[113]), "+f"(d[114]), "+f"(d[115]), "+f"(d[116]), "+f"(d[117]), "+f"(d[118]), "+f"(d[119]), "+f"(d[120]), "+f"(d[121]), "+f"(d[122]), "+f"(d[123]), "+f"(d[124]), "+f"(d[125]), "+f"(d[126]), "+f"(d[127])
    : "l"(da), "l"(db), "r"(sc));
}
__device__ __forceinline__ void wgmma_m64n128k16_ss(float (&d)[64], uint64_t da, uint64_t db, int sc) {
  asm volatile("{\n.reg .pred p;\nsetp.ne.b32 p, %66, 0;\n"
    "wgmma.mma_async.sync.aligned.m64n128k16.f32.bf16.bf16 {%0, %1, %2, %3, %4, %5, %6, %7, %8, %9, %10, %11, %12, %13, %14, %15, %16, %17, %18, %19, %20, %21, %22, %23, %24, %25, %26, %27, %28, %29, %30, %31, %32, %33, %34, %35, %36, %37, %38, %39, %40, %41, %42, %43, %44, %45, %46, %47, %48, %49, %50, %51, %52, %53, %54, %55, %56, %57, %58, %59, %60, %61, %62, %63}, %64, %65, p, 1, 1, 0, 0;\n}\n"
    : "+f"(d[0]), "+f"(d[1]), "+f"(d[2]), "+f"(d[3]), "+f"(d[4]), "+f"(d[5]), "+f"(d[6]), "+f"(d[7]), "+f"(d[8]), "+f"(d[9]), "+f"(d[10]), "+f"(d[11]), "+f"(d[12]), "+f"(d[13]), "+f"(d[14]), "+f"(d[15]), "+f"(d[16]), "+f"(d[17]), "+f"(d[18]), "+f"(d[19]), "+f"(d[20]), "+f"(d[21]), "+f"(d[22]), "+f"(d[23]), "+f"(d[24]), "+f"(d[25]), "+f"(d[26]), "+f"(d[27]), "+f"(d[28]), "+f"(d[29]), "+f"(d[30]), "+f"(d[31]), "+f"(d[32]), "+f"(d[33]), "+f"(d[34]), "+f"(d[35]), "+f"(d[36]), "+f"(d[37]), "+f"(d[38]), "+f"(d[39]), "+f"(d[40]), "+f"(d[41]), "+f"(d[42]), "+f"(d[43]), "+f"(d[44]), "+f"(d[45]), "+f"(d[46]), "+f"(d[47]), "+f"(d[48]), "+f"(d[49]), "+f"(d[50]), "+f"(d[51]), "+f"(d[52]), "+f"(d[53]), "+f"(d[54]), "+f"(d[55]), "+f"(d[56]), "+f"(d[57]), "+f"(d[58]), "+f"(d[59]), "+f"(d[60]), "+f"(d[61]), "+f"(d[62]), "+f"(d[63])
    : "l"(da), "l"(db), "r"(sc));
}
__device__ __forceinline__ void wgmma_m64n256k16_rs_tb(float (&d)[128], uint32_t a0, uint32_t a1, uint32_t a2, uint32_t a3, uint64_t db, int sc) {
  asm volatile("{\n.reg .pred p;\nsetp.ne.b32 p, %133, 0;\n"
    "wgmma.mma_async.sync.aligned.m64n256k16.f32.bf16.bf16 {%0, %1, %2, %3, %4, %5, %6, %7, %8, %9, %10, %11, %12, %13, %14, %15, %16, %17, %18, %19, %20, %21, %22, %23, %24, %25, %26, %27, %28, %29, %30, %31, %32, %33, %34, %35, %36, %37, %38, %39, %40, %41, %42, %43, %44, %45, %46, %47, %48, %49, %50, %51, %52, %53, %54, %55, %56, %57, %58, %59, %60, %61, %62, %63, %64, %65, %66, %67, %68, %69, %70, %71, %72, %73, %74, %75, %76, %77, %78, %79, %80, %81, %82, %83, %84, %85, %86, %87, %88, %89, %90, %91, %92, %93, %94, %95, %96, %97, %98, %99, %100, %101, %102, %103, %104, %105, %106, %107, %108, %109, %110, %111, %112, %113, %114, %115, %116, %117, %118, %119, %120, %121, %122, %123, %124, %125, %126, %127}, {%128, %129, %130, %131}, %132, p, 1, 1, 1;\n}\n"
    : "+f"(d[0]), "+f"(d[1]), "+f"(d[2]), "+f"(d[3]), "+f"(d[4]), "+f"(d[5]), "+f"(d[6]), "+f"(d[7]), "+f"(d[8]), "+f"(d[9]), "+f"(d[10]), "+f"(d[11]), "+f"(d[12]), "+f"(d[13]), "+f"(d[14]), "+f"(d[15]), "+f"(d[16]), "+f"(d[17]), "+f"(d[18]), "+f"(d[19]), "+f"(d[20]), "+f"(d[21]), "+f"(d[22]), "+f"(d[23]), "+f"(d[24]), "+f"(d[25]), "+f"(d[26]), "+f"(d[27]), "+f"(d[28]), "+f"(d[29]), "+f"(d[30]), "+f"(d[31]), "+f"(d[32]), "+f"(d[33]), "+f"(d[34]), "+f"(d[35]), "+f"(d[36]), "+f"(d[37]), "+f"(d[38]), "+f"(d[39]), "+f"(d[40]), "+f"(d[41]), "+f"(d[42]), "+f"(d[43]), "+f"(d[44]), "+f"(d[45]), "+f"(d[46]), "+f"(d[47]), "+f"(d[48]), "+f"(d[49]), "+f"(d[50]), "+f"(d[51]), "+f"(d[52]), "+f"(d[53]), "+f"(d[54]), "+f"(d[55]), "+f"(d[56]), "+f"(d[57]), "+f"(d[58]), "+f"(d[59]), "+f"(d[60]), "+f"(d[61]), "+f"(d[62]), "+f"(d[63]), "+f"(d[64]), "+f"(d[65]), "+f"(d[66]), "+f"(d[67]), "+f"(d[68]), "+f"(d[69]), "+f"(d[70]), "+f"(d[71]), "+f"(d[72]), "+f"(d[73]), "+f"(d[74]), "+f"(d[75]), "+f"(d[76]), "+f"(d[77]), "+f"(d[78]), "+f"(d[79]), "+f"(d[80]), "+f"(d[81]), "+f"(d[82]), "+f"(d[83]), "+f"(d[84]), "+f"(d[85]), "+f"(d[86]), "+f"(d[87]), "+f"(d[88]), "+f"(d[89]), "+f"(d[90]), "+f"(d[91]), "+f"(d[92]), "+f"(d[93]), "+f"(d[94]), "+f"(d[95]), "+f"(d[96]), "+f"(d[97]), "+f"(d[98]), "+f"(d[99]), "+f"(d[100]), "+f"(d[101]), "+f"(d[102]), "+f"(d[103]), "+f"(d[104]), "+f"(d[105]), "+f"(d[106]), "+f"(d[107]), "+f"(d[108]), "+f"(d[109]), "+f"(d[110]), "+f"(d[111]), "+f"(d[112]), "+f"(d[113]), "+f"(d[114]), "+f"(d[115]), "+f"(d[116]), "+f"(d[117]), "+f"(d[118]), "+f"(d[119]), "+f"(d[120]), "+f"(d[121]), "+f"(d[122]), "+f"(d[123]), "+f"(d[124]), "+f"(d[125]), "+f"(d[126]), "+f"(d[127])
    : "r"(a0), "r"(a1), "r"(a2), "r"(a3), "l"(db), "r"(sc));
}
__device__ __forceinline__ void wgmma_m64n128k16_ss_tb(float (&d)[64], uint64_t da, uint64_t db, int sc) {
  asm volatile("{\n.reg .pred p;\nsetp.ne.b32 p, %66, 0;\n"
    "wgmma.mma_async.sync.aligned.m64n128k16.f32.bf16.bf16 {%0, %1, %2, %3, %4, %5, %6, %7, %8, %9, %10, %11, %12, %13, %14, %15, %16, %17, %18, %19, %20, %21, %22, %23, %24, %25, %26, %27, %28, %29, %30, %31, %32, %33, %34, %35, %36, %37, %38, %39, %40, %41, %42, %43, %44, %45, %46, %47, %48, %49, %50, %51, %52, %53, %54, %55, %56, %57, %58, %59, %60, %61, %62, %63}, %64, %65, p, 1, 1, 0, 1;\n}\n"
    : "+f"(d[0]), "+f"(d[1]), "+f"(d[2]), "+f"(d[3]), "+f"(d[4]), "+f"(d[5]), "+f"(d[6]), "+f"(d[7]), "+f"(d[8]), "+f"(d[9]), "+f"(d[10]), "+f"(d[11]), "+f"(d[12]), "+f"(d[13]), "+f"(d[14]), "+f"(d[15]), "+f"(d[16]), "+f"(d[17]), "+f"(d[18]), "+f"(d[19]), "+f"(d[20]), "+f"(d[21]), "+f"(d[22]), "+f"(d[23]), "+f"(d[24]), "+f"(d[25]), "+f"(d[26]), "+f"(d[27]), "+f"(d[28]), "+f"(d[29]), "+f"(d[30]), "+f"(d[31]), "+f"(d[32]), "+f"(d[33]), "+f"(d[34]), "+f"(d[35]), "+f"(d[36]), "+f"(d[37]), "+f"(d[38]), "+f"(d[39]), "+f"(d[40]), "+f"(d[41]), "+f"(d[42]), "+f"(d[43]), "+f"(d[44]), "+f"(d[45]), "+f"(d[46]), "+f"(d[47]), "+f"(d[48]), "+f"(d[49]), "+f"(d[50]), "+f"(d[51]), "+f"(d[52]), "+f"(d[53]), "+f"(d[54]), "+f"(d[55]), "+f"(d[56]), "+f"(d[57]), "+f"(d[58]), "+f"(d[59]), "+f"(d[60]), "+f"(d[61]), "+f"(d[62]), "+f"(d[63])
    : "l"(da), "l"(db), "r"(sc));
}
__device__ __forceinline__ void wgmma_m64n128k16_rs_tb(float (&d)[64], uint32_t a0, uint32_t a1, uint32_t a2, uint32_t a3, uint64_t db, int sc) {
  asm volatile("{\n.reg .pred p;\nsetp.ne.b32 p, %69, 0;\n"
    "wgmma.mma_async.sync.aligned.m64n128k16.f32.bf16.bf16 {%0, %1, %2, %3, %4, %5, %6, %7, %8, %9, %10, %11, %12, %13, %14, %15, %16, %17, %18, %19, %20, %21, %22, %23, %24, %25, %26, %27, %28, %29, %30, %31, %32, %33, %34, %35, %36, %37, %38, %39, %40, %41, %42, %43, %44, %45, %46, %47, %48, %49, %50, %51, %52, %53, %54, %55, %56, %57, %58, %59, %60, %61, %62, %63}, {%64, %65, %66, %67}, %68, p, 1, 1, 1;\n}\n"
    : "+f"(d[0]), "+f"(d[1]), "+f"(d[2]), "+f"(d[3]), "+f"(d[4]), "+f"(d[5]), "+f"(d[6]), "+f"(d[7]), "+f"(d[8]), "+f"(d[9]), "+f"(d[10]), "+f"(d[11]), "+f"(d[12]), "+f"(d[13]), "+f"(d[14]), "+f"(d[15]), "+f"(d[16]), "+f"(d[17]), "+f"(d[18]), "+f"(d[19]), "+f"(d[20]), "+f"(d[21]), "+f"(d[22]), "+f"(d[23]), "+f"(d[24]), "+f"(d[25]), "+f"(d[26]), "+f"(d[27]), "+f"(d[28]), "+f"(d[29]), "+f"(d[30]), "+f"(d[31]), "+f"(d[32]), "+f"(d[33]), "+f"(d[34]), "+f"(d[35]), "+f"(d[36]), "+f"(d[37]), "+f"(d[38]), "+f"(d[39]), "+f"(d[40]), "+f"(d[41]), "+f"(d[42]), "+f"(d[43]), "+f"(d[44]), "+f"(d[45]), "+f"(d[46]), "+f"(d[47]), "+f"(d[48]), "+f"(d[49]), "+f"(d[50]), "+f"(d[51]), "+f"(d[52]), "+f"(d[53]), "+f"(d[54]), "+f"(d[55]), "+f"(d[56]), "+f"(d[57]), "+f"(d[58]), "+f"(d[59]), "+f"(d[60]), "+f"(d[61]), "+f"(d[62]), "+f"(d[63])
    : "r"(a0), "r"(a1), "r"(a2), "r"(a3), "l"(db), "r"(sc));
}
__device__ __forceinline__ void wgmma_m64n64k16_ss_tb(float (&d)[32], uint64_t da, uint64_t db, int sc) {
  asm volatile("{\n.reg .pred p;\nsetp.ne.b32 p, %34, 0;\n"
    "wgmma.mma_async.sync.aligned.m64n64k16.f32.bf16.bf16 {%0, %1, %2, %3, %4, %5, %6, %7, %8, %9, %10, %11, %12, %13, %14, %15, %16, %17, %18, %19, %20, %21, %22, %23, %24, %25, %26, %27, %28, %29, %30, %31}, %32, %33, p, 1, 1, 0, 1;\n}\n"
    : "+f"(d[0]), "+f"(d[1]), "+f"(d[2]), "+f"(d[3]), "+f"(d[4]), "+f"(d[5]), "+f"(d[6]), "+f"(d[7]), "+f"(d[8]), "+f"(d[9]), "+f"(d[10]), "+f"(d[11]), "+f"(d[12]), "+f"(d[13]), "+f"(d[14]), "+f"(d[15]), "+f"(d[16]), "+f"(d[17]), "+f"(d[18]), "+f"(d[19]), "+f"(d[20]), "+f"(d[21]), "+f"(d[22]), "+f"(d[23]), "+f"(d[24]), "+f"(d[25]), "+f"(d[26]), "+f"(d[27]), "+f"(d[28]), "+f"(d[29]), "+f"(d[30]), "+f"(d[31])
    : "l"(da), "l"(db), "r"(sc));
}
__device__ __forceinline__ void wgmma_m64n64k16_rs_tb(float (&d)[32], uint32_t a0, uint32_t a1, uint32_t a2, uint32_t a3, uint64_t db, int sc) {
  asm volatile("{\n.reg .pred p;\nsetp.ne.b32 p, %37, 0;\n"
    "wgmma.mma_async.sync.aligned.m64n64k16.f32.bf16.bf16 {%0, %1, %2, %3, %4, %5, %6, %7, %8, %9, %10, %11, %12, %13, %14, %15, %16, %17, %18, %19, %20, %21, %22, %23, %24, %25, %26, %27, %28, %29, %30, %31}, {%32, %33, %34, %35}, %36, p, 1, 1, 1;\n}\n"
    : "+f"(d[0]), "+f"(d[1]), "+f"(d[2]), "+f"(d[3]), "+f"(d[4]), "+f"(d[5]), "+f"(d[6]), "+f"(d[7]), "+f"(d[8]), "+f"(d[9]), "+f"(d[10]), "+f"(d[11]), "+f"(d[12]), "+f"(d[13]), "+f"(d[14]), "+f"(d[15]), "+f"(d[16]), "+f"(d[17]), "+f"(d[18]), "+f"(d[19]), "+f"(d[20]), "+f"(d[21]), "+f"(d[22]), "+f"(d[23]), "+f"(d[24]), "+f"(d[25]), "+f"(d[26]), "+f"(d[27]), "+f"(d[28]), "+f"(d[29]), "+f"(d[30]), "+f"(d[31])
    : "r"(a0), "r"(a1), "r"(a2), "r"(a3), "l"(db), "r"(sc));
}
__device__ __forceinline__ void wgmma_m64n192k16_ss_tb(float (&d)[128], uint64_t da, uint64_t db, int sc) {
  asm volatile("{\n.reg .pred p;\nsetp.ne.b32 p, %98, 0;\n"
    "wgmma.mma_async.sync.aligned.m64n192k16.f32.bf16.bf16 {%0, %1, %2, %3, %4, %5, %6, %7, %8, %9, %10, %11, %12, %13, %14, %15, %16, %17, %18, %19, %20, %21, %22, %23, %24, %25, %26, %27, %28, %29, %30, %31, %32, %33, %34, %35, %36, %37, %38, %39, %40, %41, %42, %43, %44, %45, %46, %47, %48, %49, %50, %51, %52, %53, %54, %55, %56, %57, %58, %59, %60, %61, %62, %63, %64, %65, %66, %67, %68, %69, %70, %71, %72, %73, %74, %75, %76, %77, %78, %79, %80, %81, %82, %83, %84, %85, %86, %87, %88, %89, %90, %91, %92, %93, %94, %95}, %96, %97, p, 1, 1, 0, 1;\n}\n"
    : "+f"(d[0]), "+f"(d[1]), "+f"(d[2]), "+f"(d[3]), "+f"(d[4]), "+f"(d[5]), "+f"(d[6]), "+f"(d[7]), "+f"(d[8]), "+f"(d[9]), "+f"(d[10]), "+f"(d[11]), "+f"(d[12]), "+f"(d[13]), "+f"(d[14]), "+f"(d[15]), "+f"(d[16]), "+f"(d[17]), "+f"(d[18]), "+f"(d[19]), "+f"(d[20]), "+f"(d[21]), "+f"(d[22]), "+f"(d[23]), "+f"(d[24]), "+f"(d[25]), "+f"(d[26]), "+f"(d[27]), "+f"(d[28]), "+f"(d[29]), "+f"(d[30]), "+f"(d[31]), "+f"(d[32]), "+f"(d[33]), "+f"(d[34]), "+f"(d[35]), "+f"(d[36]), "+f"(d[37]), "+f"(d[38]), "+f"(d[39]), "+f"(d[40]), "+f"(d[41]), "+f"(d[42]), "+f"(d[43]), "+f"(d[44]), "+f"(d[45]), "+f"(d[46]), "+f"(d[47]), "+f"(d[48]), "+f"(d[49]), "+f"(d[50]), "+f"(d[51]), "+f"(d[52]), "+f"(d[53]), "+f"(d[54]), "+f"(d[55]), "+f"(d[56]), "+f"(d[57]), "+f"(d[58]), "+f"(d[59]), "+f"(d[60]), "+f"(d[61]), "+f"(d[62]), "+f"(d[63]), "+f"(d[64]), "+f"(d[65]), "+f"(d[66]), "+f"(d[67]), "+f"(d[68]), "+f"(d[69]), "+f"(d[70]), "+f"(d[71]), "+f"(d[72]), "+f"(d[73]), "+f"(d[74]), "+f"(d[75]), "+f"(d[76]), "+f"(d[77]), "+f"(d[78]), "+f"(d[79]), "+f"(d[80]), "+f"(d[81]), "+f"(d[82]), "+f"(d[83]), "+f"(d[84]), "+f"(d[85]), "+f"(d[86]), "+f"(d[87]), "+f"(d[88]), "+f"(d[89]), "+f"(d[90]), "+f"(d[91]), "+f"(d[92]), "+f"(d[93]), "+f"(d[94]), "+f"(d[95])
    : "l"(da), "l"(db), "r"(sc));
}

#define TM(id)
#define GT_MIN(i)
#define GT_MAX(i)

constexpr int NS = 5;
constexpr uint32_t STG = 32768;
constexpr uint32_t SM_Q = 0;
constexpr uint32_t SM_RING = 65536;
constexpr uint32_t SM_BAR = SM_RING + NS * STG;
constexpr uint32_t SM_TOTAL = SM_BAR + 256 + 1024;

struct Ring {
  uint32_t base, full0, empty0, st, ph, nst, stg;
  __device__ __forceinline__ void init(uint32_t sb) { base = sb + SM_RING; full0 = sb + SM_BAR; empty0 = sb + SM_BAR + 64; st = 0; ph = 0; nst = NS; stg = STG; }
  __device__ __forceinline__ uint32_t phase() const { return (ph >> st) & 1; }
  __device__ __forceinline__ uint32_t buf() const { return base + st * stg; }
  __device__ __forceinline__ uint32_t full() const { return full0 + st * 8; }
  __device__ __forceinline__ uint32_t empty() const { return empty0 + st * 8; }
  __device__ __forceinline__ void next() { ph ^= 1u << st; st = (st + 1 >= nst) ? 0 : st + 1; }
  __device__ __forceinline__ void shrink() { nst = NS - 1; if (st >= nst) st = 0; }
  __device__ __forceinline__ uint32_t acquire(uint32_t bytes) {
    mbar_wait(empty(), phase() ^ 1); mbar_expect_tx(full(), bytes); return buf();
  }
  __device__ __forceinline__ uint32_t wait() { mbar_wait(full(), phase()); return buf(); }
};
template <int CL = 2>
__device__ __forceinline__ void ring_release(uint32_t empty_bar, int lane) {
  __syncwarp();
  if (lane < CL) mbar_arrive_remote(empty_bar, (uint32_t)lane);
}

template <int CL>
__device__ __forceinline__ void gemm_k448_n256(Ring& r, float (&acc)[128], int wg, int lane) {
  uint32_t hb = 0, hrel = 0, prel = 0, phrel = 0;
#pragma unroll
  for (int c = 0; c < 7; ++c) {
    if ((c & 1) == 0) { hb = r.wait(); hrel = r.empty(); r.next(); }
    uint32_t wb = r.wait(); uint32_t wrel = r.empty(); r.next();
    uint64_t da = mk_desc(hb + (c & 1) * 16384 + wg * 8192, 16, 1024);
    uint64_t db = mk_desc(wb, 8192, 1024);
    wg_fence();
#pragma unroll
    for (int k = 0; k < 4; ++k) wgmma_m64n256k16_ss_tb(acc, da + k * 2, db + k * 128, (c | k) != 0);
    wg_commit();
    if (c > 0) {
      wg_wait<1>();
      ring_release<CL>(prel, lane);
      if ((c & 1) == 0) ring_release<CL>(phrel, lane);
    }
    prel = wrel; phrel = hrel;
  }
  wg_wait<0>();
  ring_release<CL>(prel, lane); ring_release<CL>(phrel, lane);
}

template <bool RELU>
__device__ __forceinline__ void store_tile_bf16(uint32_t base, const float (&acc)[128], int rloc, int t4) {
  uint32_t row0 = base + rloc * 128, row1 = row0 + 8 * 128;
  uint32_t sw = (uint32_t)(rloc & 7);
#pragma unroll
  for (int j = 0; j < 32; ++j) {
    uint32_t off = (uint32_t)(j >> 3) * 16384 + ((((uint32_t)j & 7) ^ sw) << 4) + t4 * 4;
    float a = acc[4 * j], b = acc[4 * j + 1], c = acc[4 * j + 2], d = acc[4 * j + 3];
    if (RELU) { a = fmaxf(a, 0.f); b = fmaxf(b, 0.f); c = fmaxf(c, 0.f); d = fmaxf(d, 0.f); }
    asm volatile("st.shared.b32 [%0], %1;" ::"r"(row0 + off), "r"(pack_bf16(a, b)) : "memory");
    asm volatile("st.shared.b32 [%0], %1;" ::"r"(row1 + off), "r"(pack_bf16(c, d)) : "memory");
  }
}

template <int NJ, int OFF = 0, int SZ = 64, bool WAIT = true>
__device__ __forceinline__ void red_rows(uint32_t stg, const CUtensorMap* tm, int row0, int col0, const float (&a)[SZ], int sel, int lane) {
  asm volatile("" : "+r"(stg), "+r"(lane));
  if (WAIT) {
    if (lane == 0) asm volatile("cp.async.bulk.wait_group.read 0;" ::: "memory");
    __syncwarp();
  }
  const uint32_t g = lane >> 2, t4 = lane & 3;
  const uint32_t wbase = stg + g * 128 + (t4 & 1) * 8;
#pragma unroll
  for (int j = 0; j < NJ; ++j)
    asm volatile("st.shared.v2.f32 [%0], {%1, %2};" ::"r"(wbase + (j >> 2) * 1024 + ((((j & 3) * 2 + (t4 >> 1)) ^ g) << 4)),
                 "f"(a[OFF + 4 * j + sel]), "f"(a[OFF + 4 * j + sel + 1]) : "memory");
  fence_async_smem();
  __syncwarp();
  if (lane == 0) {
#pragma unroll
    for (int b = 0; b < NJ / 4; ++b)
      asm volatile("cp.reduce.async.bulk.tensor.2d.global.shared::cta.add.tile.bulk_group [%0, {%2, %3}], [%1];"
                   ::"l"(tm), "r"(stg + b * 1024), "r"(col0 + b * 32), "r"(row0) : "memory");
    asm volatile("cp.async.bulk.commit_group;" ::: "memory");
  }
}

template <int NSM, int NRG, int CL>
__device__ __forceinline__ void out_proj(Ring& r, const uint32_t (&ob)[64], uint32_t abase,
                                         const CUtensorMap* tm, int roww, uint32_t stg, int lane) {
  constexpr int NST = (NSM + NRG) / 2;
  uint32_t prel = 0;
  float accA[64], accB[64];
  float(&cur32)[32] = *reinterpret_cast<float(*)[32]>(&accB[0]);
#pragma unroll
  for (int pass = 0; pass < 4; ++pass) {
    float(&cur)[64] = (pass & 1) ? accB : accA;
    float(&prv)[64] = (pass & 1) ? accA : accB;
#pragma unroll
    for (int st = 0; st < NST; ++st) {
      uint32_t wb = r.wait(); uint32_t rel = r.empty(); r.next();
      asm volatile("" : "+r"(abase));
      wg_fence();
#pragma unroll
      for (int cc = 0; cc < 2; ++cc) {
        const int c = 2 * st + cc;
#pragma unroll
        for (int k = 0; k < 4; ++k) {
          const int sc = (c | k) != 0;
          if (pass < 3) {
            uint64_t db = mk_desc(wb + cc * 16384 + k * 2048, 8192, 1024);
            if (c < NSM) wgmma_m64n128k16_ss_tb(cur, mk_desc(abase + c * 16384 + k * 32, 16, 1024), db, sc);
            else { const int o = (c - NSM) * 16 + 4 * k; wgmma_m64n128k16_rs_tb(cur, ob[o], ob[o + 1], ob[o + 2], ob[o + 3], db, sc); }
          } else {
            uint64_t db = mk_desc(wb + cc * 8192 + k * 2048, 8192, 1024);
            if (c < NSM) wgmma_m64n64k16_ss_tb(cur32, mk_desc(abase + c * 16384 + k * 32, 16, 1024), db, sc);
            else { const int o = (c - NSM) * 16 + 4 * k; wgmma_m64n64k16_rs_tb(cur32, ob[o], ob[o + 1], ob[o + 2], ob[o + 3], db, sc); }
          }
        }
      }
      wg_commit();
      if (pass | st) { wg_wait<1>(); ring_release<CL>(prel, lane); }
      prel = rel;
      if (pass > 0) {
        if (st == 0) red_rows<16>(stg, tm, roww, (pass - 1) * 128, prv, 0, lane);
        if (st == NST / 2) red_rows<16>(stg, tm, roww + 8, (pass - 1) * 128, prv, 2, lane);
      }
    }
  }
  wg_wait<0>(); ring_release<CL>(prel, lane);
  red_rows<8>(stg, tm, roww, 384, accB, 0, lane);
  red_rows<8>(stg, tm, roww + 8, 384, accB, 2, lane);
  if (lane == 0) asm volatile("cp.async.bulk.wait_group 0;" ::: "memory");
}
template <int CL>
__device__ __forceinline__ void out_proj_loads(Ring& r, const CUtensorMap* tm, int krow0, int nch, uint32_t rank) {
  r.shrink();
  constexpr uint16_t MASK = (1 << CL) - 1;
  for (int pass = 0; pass < 4; ++pass)
    for (int st = 0; st < nch / 2; ++st) {
      if (pass < 3) {
        uint32_t b = r.acquire(32768);
        for (int x = 0; x < 4 / CL; ++x) {
          const int bx = rank * (4 / CL) + x;
          tma_load_mc(b + bx * 8192, tm, pass * 128 + (bx & 1) * 64, krow0 + (2 * st + (bx >> 1)) * 64, r.full(), MASK);
        }
      } else {
        uint32_t b = r.acquire(16384);
        if (CL == 1) { for (int x = 0; x < 2; ++x) tma_load_mc(b + x * 8192, tm, 384, krow0 + (2 * st + x) * 64, r.full(), MASK); }
        else if (rank < 2) tma_load_mc(b + rank * 8192, tm, 384, krow0 + (2 * st + rank) * 64, r.full(), MASK);
      }
      r.next();
    }
}

#define ACL 2
__global__ void __cluster_dims__(ACL, 1, 1) __launch_bounds__(384, 1)
attn_kernel(const __grid_constant__ CUtensorMap tm_h, const __grid_constant__ CUtensorMap tm_wq,
            const __grid_constant__ CUtensorMap tm_k, const __grid_constant__ CUtensorMap tm_v,
            const __grid_constant__ CUtensorMap tm_wo, const __grid_constant__ CUtensorMap tm_oA,
            const __grid_constant__ CUtensorMap tm_oAs, const __grid_constant__ CUtensorMap tm_acc) {
  extern __shared__ uint8_t smem_raw[];
  const uint32_t sb = (smem_u32(smem_raw) + 1023) & ~1023u;
  const int tid = threadIdx.x, wg = tid >> 7, lane = tid & 31;
  const int qt = blockIdx.x, kvh = blockIdx.y;
  const uint32_t rank = cluster_rank();
  Ring r; r.init(sb);
  const uint32_t bar_oA = sb + SM_BAR + 128, bar_oAf = sb + SM_BAR + 136;
  if (tid == 0) {
    for (int i = 0; i < NS; ++i) { mbar_init(r.full0 + 8 * i, 1); mbar_init(r.empty0 + 8 * i, 8 * ACL); }
    mbar_init(bar_oA, 256); mbar_init(bar_oAf, 1);
    asm volatile("fence.mbarrier_init.release.cluster;" ::: "memory");
  }
  cluster_sync_all();

  if (wg == 2) {
    asm volatile("setmaxnreg.dec.sync.aligned.u32 24;");
    if (tid == 256) {
      const int krow0 = kvh * SKV + (SKV - WIN);
      for (int hh = 0; hh < 2; ++hh) {
        const int head = kvh * 2 + hh;
        for (int p = 0; p < 4; ++p) {
          int nc = (p < 3) ? 2 : 1;
          uint32_t b = r.acquire(nc * 16384);
          const uint32_t hb = b, hf = r.full();
          const bool first = (hh | p) == 0;
          if (!first) for (int c = 0; c < nc; ++c) tma_load(hb + c * 16384, &tm_h, (2 * p + c) * 64, qt * 128, hf);
          r.next();
          for (int c = 0; c < nc; ++c) {
            b = r.acquire(32768);
            for (int x = 0; x < 4 / ACL; ++x) {
              int bx = rank * 2 + x;
              tma_load_mc(b + bx * 8192, &tm_wq, head * 256 + bx * 64, (2 * p + c) * 64, r.full(), (1 << ACL) - 1);
            }
            r.next();
          }
          if (first) {
            pdl_wait();
            GT_MIN(4);
            for (int c = 0; c < nc; ++c) tma_load(hb + c * 16384, &tm_h, (2 * p + c) * 64, qt * 128, hf);
          }
        }
        for (int t = 0; t < 4; ++t) {
          for (int hf = 0; hf < 2; ++hf) {
            uint32_t b = r.acquire(32768);
            for (int x = 0; x < 2 / ACL; ++x)
              tma_load_mc(b + (rank + x) * 16384, &tm_k, (2 * hf + rank + x) * 64, krow0 + t * 128, r.full(), (1 << ACL) - 1);
            r.next();
          }
          for (int hf = 0; hf < 2; ++hf) {
            uint32_t b = r.acquire(32768);
            for (int x = 0; x < 4 / ACL; ++x) {
              int bx = rank * 2 + x;
              tma_load_mc(b + bx * 8192, &tm_v, bx * 64, krow0 + t * 128 + hf * 64, r.full(), (1 << ACL) - 1);
            }
            r.next();
          }
        }
      }
      mbar_wait(bar_oA, 0);
      mbar_expect_tx(bar_oAf, 65536);
      for (int c = 0; c < 4; ++c) tma_load(sb + SM_Q + c * 16384, &tm_oA, c * 64, kvh * SEQ + qt * 128, bar_oAf);
      out_proj_loads<ACL>(r, &tm_wo, kvh * 512, 8, rank);
    }
  } else {
    asm volatile("setmaxnreg.inc.sync.aligned.u32 240;");
    const int warp = (tid >> 5) & 3, g = lane >> 2, t4 = lane & 3;
    const int rloc = wg * 64 + warp * 16 + g;
    uint32_t ob[64];
    float acc[128];
    const float CS = 1.4426950408889634f * 0.0625f;
    TM(0);
#pragma unroll 1
    for (int hh = 0; hh < 2; ++hh) {
      gemm_k448_n256<ACL>(r, acc, wg, lane);
      TM(1);
      if (hh == 1) {
        if ((tid & 127) == 0) asm volatile("cp.async.bulk.wait_group.read 0;" ::: "memory");
        bar_sync(1 + wg, 128);
      }
      store_tile_bf16<false>(sb + SM_Q, acc, rloc, t4);
      fence_async_smem();
      bar_sync(1 + wg, 128);
      float m0 = -INFINITY, m1 = -INFINITY, l0 = 0.f, l1 = 0.f;
      const uint32_t qa0 = sb + SM_Q + wg * 8192;
      if (wg == 1) bar_arrive(3, 256);
      TM(2);
      bar_sync(3 + wg, 256);
#pragma unroll 1
      for (int t = 0; t < 4; ++t) {
        float s[64];
        TM(3);
        {
          uint32_t qa = qa0; asm volatile("" : "+r"(qa));
          uint32_t ka = r.wait(); uint32_t rel0 = r.empty(); r.next();
          wg_fence();
#pragma unroll
          for (int k = 0; k < 8; ++k)
            wgmma_m64n128k16_ss(s, mk_desc(qa + (k >> 2) * 16384 + (k & 3) * 32, 16, 1024),
                                mk_desc(ka + (k >> 2) * 16384 + (k & 3) * 32, 16, 1024), k != 0);
          wg_commit();
          uint32_t kb = r.wait(); uint32_t rel1 = r.empty(); r.next();
          wg_fence();
#pragma unroll
          for (int k = 0; k < 8; ++k)
            wgmma_m64n128k16_ss(s, mk_desc(qa + (2 + (k >> 2)) * 16384 + (k & 3) * 32, 16, 1024),
                                mk_desc(kb + (k >> 2) * 16384 + (k & 3) * 32, 16, 1024), 1);
          wg_commit();
          bar_arrive(4 - wg, 256);
          wg_wait<1>(); ring_release<ACL>(rel0, lane);
          wg_wait<0>(); ring_release<ACL>(rel1, lane);
        }
        TM(4);
        float mx0 = m0, mx1 = m1;
#pragma unroll
        for (int j = 0; j < 16; ++j) {
          uint32_t a = pack_bf16(s[4 * j], s[4 * j + 1]), b = pack_bf16(s[4 * j + 2], s[4 * j + 3]);
          s[4 * j] = bf_lo(a); s[4 * j + 1] = bf_hi(a); s[4 * j + 2] = bf_lo(b); s[4 * j + 3] = bf_hi(b);
          mx0 = fmaxf(mx0, fmaxf(s[4 * j], s[4 * j + 1])); mx1 = fmaxf(mx1, fmaxf(s[4 * j + 2], s[4 * j + 3]));
        }
        mx0 = fmaxf(mx0, __shfl_xor_sync(0xffffffffu, mx0, 1)); mx0 = fmaxf(mx0, __shfl_xor_sync(0xffffffffu, mx0, 2));
        mx1 = fmaxf(mx1, __shfl_xor_sync(0xffffffffu, mx1, 1)); mx1 = fmaxf(mx1, __shfl_xor_sync(0xffffffffu, mx1, 2));
        const float c0 = ex2((m0 - mx0) * CS), c1 = ex2((m1 - mx1) * CS);
        m0 = mx0; m1 = mx1;
        const float nb0 = -mx0 * CS, nb1 = -mx1 * CS;
        float ps0 = 0.f, ps1 = 0.f;
        uint32_t pa[32];
#pragma unroll
        for (int j = 0; j < 16; ++j) {
          float e0 = ex2(fmaf(s[4 * j], CS, nb0)), e1 = ex2(fmaf(s[4 * j + 1], CS, nb0));
          float e2 = ex2(fmaf(s[4 * j + 2], CS, nb1)), e3 = ex2(fmaf(s[4 * j + 3], CS, nb1));
          ps0 += e0 + e1; ps1 += e2 + e3;
          pa[2 * j] = pack_bf16(e0, e1); pa[2 * j + 1] = pack_bf16(e2, e3);
        }
        l0 = l0 * c0 + ps0; l1 = l1 * c1 + ps1;
        if (t > 0) {
#pragma unroll
          for (int j = 0; j < 32; ++j) { acc[4 * j] *= c0; acc[4 * j + 1] *= c0; acc[4 * j + 2] *= c1; acc[4 * j + 3] *= c1; }
        }
#pragma unroll
        for (int j = 0; j < 32; ++j) asm volatile("" : "+r"(pa[j]));
#pragma unroll
        for (int j = 0; j < 128; ++j) asm volatile("" : "+f"(acc[j]));
        asm volatile("" : "+f"(l0), "+f"(l1));
        TM(5);
        bar_sync(3 + wg, 256);
        TM(6);
        {
          uint32_t va = r.wait(); uint32_t rel0 = r.empty(); r.next();
          wg_fence();
#pragma unroll
          for (int k = 0; k < 4; ++k)
            wgmma_m64n256k16_rs_tb(acc, pa[4 * k], pa[4 * k + 1], pa[4 * k + 2], pa[4 * k + 3],
                                   mk_desc(va + k * 2048, 8192, 1024), (t | k) != 0);
          wg_commit();
          uint32_t vb = r.wait(); uint32_t rel1 = r.empty(); r.next();
          wg_fence();
#pragma unroll
          for (int k = 0; k < 4; ++k)
            wgmma_m64n256k16_rs_tb(acc, pa[16 + 4 * k], pa[16 + 4 * k + 1], pa[16 + 4 * k + 2], pa[16 + 4 * k + 3],
                                   mk_desc(vb + k * 2048, 8192, 1024), 1);
          wg_commit();
          if (t == 3 && wg == 0) bar_arrive(4, 256);
          wg_wait<1>(); ring_release<ACL>(rel0, lane);
          wg_wait<0>(); ring_release<ACL>(rel1, lane);
        }
      }
      TM(7);
      l0 += __shfl_xor_sync(0xffffffffu, l0, 1); l0 += __shfl_xor_sync(0xffffffffu, l0, 2);
      l1 += __shfl_xor_sync(0xffffffffu, l1, 1); l1 += __shfl_xor_sync(0xffffffffu, l1, 2);
      const float i0 = 1.f / l0, i1 = 1.f / l1;
#pragma unroll
      for (int j = 0; j < 32; ++j) {
        ob[2 * j] = pack_bf16(acc[4 * j] * i0, acc[4 * j + 1] * i0);
        ob[2 * j + 1] = pack_bf16(acc[4 * j + 2] * i1, acc[4 * j + 3] * i1);
      }
      if (hh == 0) {
        uint32_t row0 = sb + SM_Q + rloc * 128, row1 = row0 + 8 * 128;
        uint32_t sw = (uint32_t)(rloc & 7);
#pragma unroll
        for (int j = 0; j < 32; ++j) {
          uint32_t off = (uint32_t)(j >> 3) * 16384 + ((((uint32_t)j & 7) ^ sw) << 4) + t4 * 4;
          asm volatile("st.shared.b32 [%0], %1;" ::"r"(row0 + off), "r"(ob[2 * j]) : "memory");
          asm volatile("st.shared.b32 [%0], %1;" ::"r"(row1 + off), "r"(ob[2 * j + 1]) : "memory");
        }
        fence_async_smem();
        bar_sync(1 + wg, 128);
        if ((tid & 127) == 0) {
          for (int c = 0; c < 4; ++c)
            asm volatile("cp.async.bulk.tensor.2d.global.shared::cta.bulk_group [%0, {%2, %3}], [%1];"
                         ::"l"(&tm_oAs), "r"(sb + SM_Q + c * 16384 + wg * 8192), "r"(c * 64), "r"(kvh * SEQ + qt * 128 + wg * 64) : "memory");
          asm volatile("cp.async.bulk.commit_group;" ::: "memory");
        }
      }
    }
    if ((tid & 127) == 0) asm volatile("cp.async.bulk.wait_group 0;" ::: "memory");
    mbar_arrive(bar_oA);
    mbar_wait(bar_oAf, 0);
    TM(8);
    r.shrink();
    out_proj<4, 4, ACL>(r, ob, sb + SM_Q + wg * 8192, &tm_acc, qt * 128 + wg * 64 + warp * 16,
                   sb + SM_RING + (NS - 1) * STG + (wg * 4 + warp) * 4096, lane);
    TM(9);
  }
  cluster_sync_all();
  GT_MAX(5);
}

constexpr uint32_t F_STG = 57344, F_A = 0, F_RING = 57344, F_BAR = F_RING + 3 * F_STG, F_TOTAL = F_BAR + 256 + 1024;

template <int WG>
__device__ __forceinline__ void ffn_gemm(Ring& r, float (&acc)[128], uint32_t abase, int lane) {
  uint32_t prel = 0;
#pragma unroll
  for (int c = 0; c < 7; ++c) {
    uint32_t wb = r.wait(); uint32_t wrel = r.empty(); r.next();
    uint64_t da = mk_desc(abase + c * 8192, 16, 1024);
    uint64_t db = mk_desc(wb + WG * 32768, 8192, 1024);
    wg_fence();
#pragma unroll
    for (int k = 0; k < 4; ++k) {
      if (WG == 0) wgmma_m64n256k16_ss_tb(acc, da + k * 2, db + k * 128, (c | k) != 0);
      else wgmma_m64n192k16_ss_tb(acc, da + k * 2, db + k * 128, (c | k) != 0);
    }
    wg_commit();
    if (c > 0) { wg_wait<1>(); ring_release<2>(prel, lane); }
    prel = wrel;
  }
  wg_wait<0>();
  ring_release<2>(prel, lane);
}

template <int WG>
__device__ __forceinline__ void ffn_consumer(Ring& r, uint32_t sb, uint32_t bar_a, int rt, int warp, int lane, const CUtensorMap* tm) {
  const int g = lane >> 2, t4 = lane & 3, row = warp * 16 + g;
  float acc[128];
  TM(20);
  mbar_wait(bar_a, 0);
  TM(21);
  ffn_gemm<WG>(r, acc, sb + F_A, lane);
  TM(22);
  bar_sync(5, 256);
  {
    uint32_t row0 = sb + F_A + WG * 32768 + row * 128, row1 = row0 + 8 * 128;
    uint32_t sw = (uint32_t)(row & 7);
#pragma unroll
    for (int j = 0; j < (WG == 0 ? 32 : 24); ++j) {
      uint32_t off = (uint32_t)(j >> 3) * 8192 + ((((uint32_t)j & 7) ^ sw) << 4) + t4 * 4;
      asm volatile("st.shared.b32 [%0], %1;" ::"r"(row0 + off), "r"(pack_bf16(fmaxf(acc[4 * j], 0.f), fmaxf(acc[4 * j + 1], 0.f))) : "memory");
      asm volatile("st.shared.b32 [%0], %1;" ::"r"(row1 + off), "r"(pack_bf16(fmaxf(acc[4 * j + 2], 0.f), fmaxf(acc[4 * j + 3], 0.f))) : "memory");
    }
  }
  fence_async_smem();
  bar_sync(5, 256);
  TM(23);
  ffn_gemm<WG>(r, acc, sb + F_A, lane);
  TM(24);
  bar_sync(5, 256);
  const int r0 = rt * 64 + warp * 16, c0 = WG * 256;
  const uint32_t stg = sb + (WG * 4 + warp) * 16384;
  red_rows<16, 0, 128, false>(stg, tm, r0, c0, acc, 0, lane);
  red_rows<16, 0, 128, false>(stg + 4096, tm, r0 + 8, c0, acc, 2, lane);
  if (WG == 0) {
    red_rows<16, 64, 128, false>(stg + 8192, tm, r0, c0 + 128, acc, 0, lane);
    red_rows<16, 64, 128, false>(stg + 12288, tm, r0 + 8, c0 + 128, acc, 2, lane);
  } else {
    red_rows<8, 64, 128, false>(stg + 8192, tm, r0, c0 + 128, acc, 0, lane);
    red_rows<8, 64, 128, false>(stg + 12288, tm, r0 + 8, c0 + 128, acc, 2, lane);
  }
  if (lane == 0) asm volatile("cp.async.bulk.wait_group 0;" ::: "memory");
  TM(25);
}

__global__ void __cluster_dims__(2, 1, 1) __launch_bounds__(384, 1)
ffn_kernel(const __grid_constant__ CUtensorMap tm_h2, const __grid_constant__ CUtensorMap tm_w1,
           const __grid_constant__ CUtensorMap tm_w2, const __grid_constant__ CUtensorMap tm_acc) {
  extern __shared__ uint8_t smem_raw[];
  const uint32_t sb = (smem_u32(smem_raw) + 1023) & ~1023u;
  const int tid = threadIdx.x, wg = tid >> 7, lane = tid & 31;
  const int rt = blockIdx.x, sl = blockIdx.y;
  const uint32_t rank = cluster_rank();
  Ring r; r.base = sb + F_RING; r.full0 = sb + F_BAR; r.empty0 = sb + F_BAR + 64; r.st = 0; r.ph = 0; r.nst = 3; r.stg = F_STG;
  const uint32_t bar_a = sb + F_BAR + 128;
  if (tid == 0) {
    for (int i = 0; i < 3; ++i) { mbar_init(r.full0 + 8 * i, 1); mbar_init(r.empty0 + 8 * i, 16); }
    mbar_init(bar_a, 1);
    asm volatile("fence.mbarrier_init.release.cluster;" ::: "memory");
  }
  cluster_sync_all();
  if (wg == 2) {
    asm volatile("setmaxnreg.dec.sync.aligned.u32 24;");
    if (tid == 256) {
      const int b0 = rank ? 4 : 0, b1 = rank ? 7 : 4;
      pdl_wait();
      mbar_expect_tx(bar_a, 57344);
      for (int k = 0; k < 7; ++k) tma_load(sb + F_A + k * 8192, &tm_h2, k * 64, rt * 64, bar_a);
      for (int c = 0; c < 14; ++c) {
        uint32_t b = r.acquire(F_STG);
        for (int bx = b0; bx < b1; ++bx) {
          if (c < 7) tma_load_mc(b + bx * 8192, &tm_w1, sl * 448 + bx * 64, c * 64, r.full(), 3);
          else tma_load_mc(b + bx * 8192, &tm_w2, bx * 64, sl * 448 + (c - 7) * 64, r.full(), 3);
        }
        r.next();
      }
    }
  } else {
    asm volatile("setmaxnreg.inc.sync.aligned.u32 240;");
    pdl_wait();
    GT_MIN(8);
    const int warp = (tid >> 5) & 3;
    if (wg == 0) ffn_consumer<0>(r, sb, bar_a, rt, warp, lane, &tm_acc);
    else ffn_consumer<1>(r, sb, bar_a, rt, warp, lane, &tm_acc);
  }
  cluster_sync_all();
  GT_MAX(9);
}

__global__ void __launch_bounds__(512) mod_kernel(const __nv_bfloat16* __restrict__ c, const __nv_bfloat16* __restrict__ wm) {
  __shared__ float red[32][33];
  const int tid = threadIdx.x;
  pdl_launch();
  GT_MIN(0);
  if (blockIdx.x < 84) {
    const int cl = tid & 15, kg = tid >> 4;
    const int col = blockIdx.x * 32 + cl * 2;
    uint32_t v[14];
#pragma unroll
    for (int i = 0; i < 14; ++i) v[i] = *reinterpret_cast<const uint32_t*>(wm + (size_t)(kg * 14 + i) * (6 * DM) + col);
    float a0 = 0.f, a1 = 0.f;
#pragma unroll
    for (int i = 0; i < 14; ++i) {
      float cv = __bfloat162float(c[kg * 14 + i]);
      float sv = rbf(cv / (1.f + __expf(-cv)));
      a0 = fmaf(sv, bf_lo(v[i]), a0); a1 = fmaf(sv, bf_hi(v[i]), a1);
    }
    red[kg][cl * 2] = a0; red[kg][cl * 2 + 1] = a1;
    __syncthreads();
    if (tid < 32) {
      float s = 0.f;
#pragma unroll
      for (int i = 0; i < 32; ++i) s += red[i][tid];
      g_mod[blockIdx.x * 32 + tid] = rbf(s);
    }
  } else {
    float4 z = make_float4(0.f, 0.f, 0.f, 0.f);
    const int n4 = SEQ * DM / 4;
    for (int i = (blockIdx.x - 84) * 512 + tid; i < n4; i += (gridDim.x - 84) * 512) {
      reinterpret_cast<float4*>(g_acc1)[i] = z; reinterpret_cast<float4*>(g_acc2)[i] = z;
    }
  }
  if (blockIdx.x < 84) GT_MAX(1); else GT_MAX(13);
}

__device__ __forceinline__ void ln_row(const float (&x)[14], const float* __restrict__ shift, const float* __restrict__ scale,
                                       __nv_bfloat16* __restrict__ out, int lane) {
  float2 sc[7], sh[7];
#pragma unroll
  for (int i = 0; i < 7; ++i) {
    sc[i] = *reinterpret_cast<const float2*>(scale + i * 64 + lane * 2);
    sh[i] = *reinterpret_cast<const float2*>(shift + i * 64 + lane * 2);
  }
  float s = 0.f;
#pragma unroll
  for (int i = 0; i < 14; ++i) s += x[i];
#pragma unroll
  for (int o = 16; o; o >>= 1) s += __shfl_xor_sync(0xffffffffu, s, o);
  const float mean = s * (1.f / DM);
  float q = 0.f;
#pragma unroll
  for (int i = 0; i < 14; ++i) { float d = x[i] - mean; q = fmaf(d, d, q); }
#pragma unroll
  for (int o = 16; o; o >>= 1) q += __shfl_xor_sync(0xffffffffu, q, o);
  const float mb = rbf(mean), vb = rbf(q * (1.f / DM));
  const float den = rbf(sqrtf(rbf(vb + 1e-5f)));
#pragma unroll
  for (int i = 0; i < 7; ++i) {
    int col = i * 64 + lane * 2;
    float y0 = rbf(rbf(x[2 * i] - mb) / den), y1 = rbf(rbf(x[2 * i + 1] - mb) / den);
    y0 = rbf(y0 * rbf(1.f + sc[i].x)); y1 = rbf(y1 * rbf(1.f + sc[i].y));
    *reinterpret_cast<uint32_t*>(out + col) = pack_bf16(y0 + sh[i].x, y1 + sh[i].y);
  }
}

__global__ void __launch_bounds__(256) ln1_kernel(const __nv_bfloat16* __restrict__ x) {
  const int lane = threadIdx.x & 31, row = blockIdx.x * 8 + (threadIdx.x >> 5);
  float v[14];
#pragma unroll
  for (int i = 0; i < 7; ++i) {
    uint32_t u = *reinterpret_cast<const uint32_t*>(x + (size_t)row * DM + i * 64 + lane * 2);
    v[2 * i] = bf_lo(u); v[2 * i + 1] = bf_hi(u);
  }
  pdl_wait();
  GT_MIN(2);
  ln_row(v, g_mod + 0 * DM, g_mod + 1 * DM, g_h + (size_t)row * DM, lane);
  GT_MAX(3);
  pdl_launch();
}

__global__ void __launch_bounds__(256) ln2_kernel(const __nv_bfloat16* __restrict__ x) {
  const int lane = threadIdx.x & 31, row = blockIdx.x * 8 + (threadIdx.x >> 5);
  float v[14];
  uint32_t xu[7];
#pragma unroll
  for (int i = 0; i < 7; ++i) xu[i] = *reinterpret_cast<const uint32_t*>(x + (size_t)row * DM + i * 64 + lane * 2);
  pdl_wait();
  GT_MIN(6);
  float2 av[7], gv[7];
#pragma unroll
  for (int i = 0; i < 7; ++i) {
    av[i] = *reinterpret_cast<const float2*>(g_acc1 + (size_t)row * DM + i * 64 + lane * 2);
    gv[i] = *reinterpret_cast<const float2*>(g_mod + 2 * DM + i * 64 + lane * 2);
  }
#pragma unroll
  for (int i = 0; i < 7; ++i) {
    int col = i * 64 + lane * 2;
    uint32_t u = xu[i];
    float t0 = rbf(gv[i].x * rbf(av[i].x)), t1 = rbf(gv[i].y * rbf(av[i].y));
    v[2 * i] = rbf(bf_lo(u) + t0); v[2 * i + 1] = rbf(bf_hi(u) + t1);
    *reinterpret_cast<uint32_t*>(g_x1 + (size_t)row * DM + col) = pack_bf16(v[2 * i], v[2 * i + 1]);
  }
  ln_row(v, g_mod + 3 * DM, g_mod + 4 * DM, g_h2 + (size_t)row * DM, lane);
  GT_MAX(7);
  pdl_launch();
}

__global__ void __launch_bounds__(256) final_kernel(__nv_bfloat16* __restrict__ out) {
  const int i = blockIdx.x * 256 + threadIdx.x;
  const int col = (i * 4) % DM;
  pdl_wait();
  GT_MIN(10);
  float4 a = reinterpret_cast<const float4*>(g_acc2)[i];
  uint2 u = reinterpret_cast<const uint2*>(g_x1)[i];
  float4 gb = *reinterpret_cast<const float4*>(g_mod + 5 * DM + col);
  uint2 o;
  o.x = pack_bf16(bf_lo(u.x) + rbf(gb.x * rbf(a.x)), bf_hi(u.x) + rbf(gb.y * rbf(a.y)));
  o.y = pack_bf16(bf_lo(u.y) + rbf(gb.z * rbf(a.z)), bf_hi(u.y) + rbf(gb.w * rbf(a.w)));
  reinterpret_cast<uint2*>(out)[i] = o;
  GT_MAX(11);
}

typedef CUresult (*EncodeFn)(CUtensorMap*, CUtensorMapDataType, cuuint32_t, void*, const cuuint64_t*, const cuuint64_t*,
                             const cuuint32_t*, const cuuint32_t*, CUtensorMapInterleave, CUtensorMapSwizzle,
                             CUtensorMapL2promotion, CUtensorMapFloatOOBfill);

static CUtensorMap make_map(EncodeFn enc, const void* ptr, uint64_t cols, uint64_t rows, uint32_t bx, uint32_t by,
                            bool f32 = false) {
  CUtensorMap m;
  cuuint64_t dims[2] = {cols, rows};
  cuuint64_t strides[1] = {cols * (f32 ? 4 : 2)};
  cuuint32_t box[2] = {bx, by};
  cuuint32_t es[2] = {1, 1};
  enc(&m, f32 ? CU_TENSOR_MAP_DATA_TYPE_FLOAT32 : CU_TENSOR_MAP_DATA_TYPE_BFLOAT16, 2, const_cast<void*>(ptr), dims, strides, box, es, CU_TENSOR_MAP_INTERLEAVE_NONE,
      CU_TENSOR_MAP_SWIZZLE_128B, CU_TENSOR_MAP_L2_PROMOTION_L2_256B, CU_TENSOR_MAP_FLOAT_OOB_FILL_NONE);
  return m;
}

template <typename... Args>
static void launch(void (*k)(Args...), dim3 grid, dim3 block, size_t smem, bool pdl, Args... args) {
  cudaLaunchConfig_t cfg = {};
  cfg.gridDim = grid; cfg.blockDim = block; cfg.dynamicSmemBytes = smem; cfg.stream = cudaStreamPerThread;
  cudaLaunchAttribute at[1];
  at[0].id = cudaLaunchAttributeProgrammaticStreamSerialization; at[0].val.programmaticStreamSerializationAllowed = 1;
  cfg.attrs = at; cfg.numAttrs = pdl ? 1 : 0;
  cudaLaunchKernelEx(&cfg, k, args...);
}

extern "C" void kernel_launch(void* const* d_in, const int* in_sizes, int n_in, void* d_out, int out_size) {
  const __nv_bfloat16* x = (const __nv_bfloat16*)d_in[0];
  const void* kc = d_in[1]; const void* vc = d_in[2]; const void* wq = d_in[3]; const void* wo = d_in[4];
  const void* w1 = d_in[6]; const void* w2 = d_in[7];
  const __nv_bfloat16* c = (const __nv_bfloat16*)d_in[8];
  const __nv_bfloat16* wm = (const __nv_bfloat16*)d_in[9];

  void* fn = nullptr; cudaDriverEntryPointQueryResult qr;
  cudaGetDriverEntryPoint("cuTensorMapEncodeTiled", &fn, cudaEnableDefault, &qr);
  EncodeFn enc = (EncodeFn)fn;
  void *p_h, *p_oA, *p_h2, *p_a1, *p_a2;
  cudaGetSymbolAddress(&p_a1, g_acc1); cudaGetSymbolAddress(&p_a2, g_acc2);
  cudaGetSymbolAddress(&p_h, g_h); cudaGetSymbolAddress(&p_oA, g_oA); cudaGetSymbolAddress(&p_h2, g_h2);
  CUtensorMap tm_h = make_map(enc, p_h, DM, SEQ, 64, 128);
  CUtensorMap tm_wq = make_map(enc, wq, 4096, DM, 64, 64);
  CUtensorMap tm_k = make_map(enc, kc, DH, HKV * SKV, 64, 128);
  CUtensorMap tm_v = make_map(enc, vc, DH, HKV * SKV, 64, 64);
  CUtensorMap tm_wo = make_map(enc, wo, DM, 4096, 64, 64);
  CUtensorMap tm_oA = make_map(enc, p_oA, DH, HKV * SEQ, 64, 128);
  CUtensorMap tm_oAs = make_map(enc, p_oA, DH, HKV * SEQ, 64, 64);
  CUtensorMap tm_a1 = make_map(enc, p_a1, DM, SEQ, 32, 8, true), tm_a2 = make_map(enc, p_a2, DM, SEQ, 32, 8, true);
  CUtensorMap tm_h2 = make_map(enc, p_h2, DM, SEQ, 64, 64);
  CUtensorMap tm_w1 = make_map(enc, w1, DFF, DM, 64, 64);
  CUtensorMap tm_w2 = make_map(enc, w2, DM, DFF, 64, 64);
  cudaFuncSetAttribute(attn_kernel, cudaFuncAttributeMaxDynamicSharedMemorySize, SM_TOTAL);
  cudaFuncSetAttribute(ffn_kernel, cudaFuncAttributeMaxDynamicSharedMemorySize, F_TOTAL);

  launch(mod_kernel, dim3(84 + 90), dim3(512), 0, false, c, wm);
  launch(ln1_kernel, dim3(SEQ / 8), dim3(256), 0, true, x);
  launch(attn_kernel, dim3(16, 8), dim3(384), SM_TOTAL, true, tm_h, tm_wq, tm_k, tm_v, tm_wo, tm_oA, tm_oAs, tm_a1);
  launch(ln2_kernel, dim3(SEQ / 8), dim3(256), 0, true, x);
  launch(ffn_kernel, dim3(32, 4), dim3(384), F_TOTAL, true, tm_h2, tm_w1, tm_w2, tm_a2);
  launch(final_kernel, dim3(SEQ * DM / 1024), dim3(256), 0, true, (__nv_bfloat16*)d_out);
}
```

```cpp
#include <cuda_runtime.h>
#include <cuda_bf16.h>
#include <cuda.h>
#include <stdint.h>

constexpr int SEQ = 2048, DM = 448, HKV = 8, SKV = 2048, DH = 256, WIN = 512, DFF = 1792;

__device__ __align__(1024) float          g_mod[6 * DM];
__device__ __align__(1024) __nv_bfloat16  g_h[SEQ * DM];
__device__ __align__(1024) __nv_bfloat16  g_oA[HKV * SEQ * DH];
__device__ __align__(1024) float          g_acc1[SEQ * DM];
__device__ __align__(1024) float          g_acc2[SEQ * DM];
__device__ __align__(1024) __nv_bfloat16  g_x1[SEQ * DM];
__device__ __align__(1024) __nv_bfloat16  g_h2[SEQ * DM];
__device__ unsigned int g_cnt[64];

__device__ __forceinline__ uint32_t smem_u32(const void* p) { return (uint32_t)__cvta_generic_to_shared(p); }
__device__ __forceinline__ void mbar_init(uint32_t bar, uint32_t cnt) {
  asm volatile("mbarrier.init.shared::cta.b64 [%0], %1;" ::"r"(bar), "r"(cnt));
}
__device__ __forceinline__ void mbar_expect_tx(uint32_t bar, uint32_t bytes) {
  asm volatile("mbarrier.arrive.expect_tx.shared::cta.b64 _, [%0], %1;" ::"r"(bar), "r"(bytes) : "memory");
}
__device__ __forceinline__ void mbar_arrive(uint32_t bar) {
  asm volatile("mbarrier.arrive.shared::cta.b64 _, [%0];" ::"r"(bar) : "memory");
}
__device__ __forceinline__ void mbar_arrive_remote(uint32_t bar, uint32_t cta) {
  asm volatile("{\n.reg .b32 ra;\nmapa.shared::cluster.u32 ra, %0, %1;\n"
               "mbarrier.arrive.shared::cluster.b64 _, [ra];\n}\n" ::"r"(bar), "r"(cta) : "memory");
}
__device__ __forceinline__ void mbar_wait(uint32_t bar, uint32_t parity) {
  asm volatile("{\n.reg .pred p;\nLAB_WAIT:\n"
               "mbarrier.try_wait.parity.shared::cta.b64 p, [%0], %1, 0x989680;\n"
               "@p bra LAB_DONE;\nbra LAB_WAIT;\nLAB_DONE:\n}\n" ::"r"(bar), "r"(parity) : "memory");
}
__device__ __forceinline__ void mbar_wait_cluster(uint32_t bar, uint32_t parity) {
  asm volatile("{\n.reg .pred p;\nLAB_WAIT:\n"
               "mbarrier.try_wait.parity.acquire.cluster.shared::cta.b64 p, [%0], %1, 0x989680;\n"
               "@p bra LAB_DONE;\nbra LAB_WAIT;\nLAB_DONE:\n}\n" ::"r"(bar), "r"(parity) : "memory");
}
__device__ __forceinline__ void tma_load(uint32_t dst, const CUtensorMap* m, int c0, int c1, uint32_t bar) {
  asm volatile("cp.async.bulk.tensor.2d.shared::cluster.global.mbarrier::complete_tx::bytes [%0], [%1, {%3, %4}], [%2];"
               ::"r"(dst), "l"(m), "r"(bar), "r"(c0), "r"(c1) : "memory");
}
__device__ __forceinline__ void tma_load_mc(uint32_t dst, const CUtensorMap* m, int c0, int c1, uint32_t bar, uint16_t mask) {
  asm volatile("cp.async.bulk.tensor.2d.shared::cluster.global.mbarrier::complete_tx::bytes.multicast::cluster [%0], [%1, {%3, %4}], [%2], %5;"
               ::"r"(dst), "l"(m), "r"(bar), "r"(c0), "r"(c1), "h"(mask) : "memory");
}
__device__ __forceinline__ void cluster_sync_all() {
  asm volatile("barrier.cluster.arrive.release.aligned;\nbarrier.cluster.wait.acquire.aligned;\n" ::: "memory");
}
__device__ __forceinline__ uint32_t cluster_rank() { uint32_t r; asm volatile("mov.u32 %0, %%cluster_ctarank;" : "=r"(r)); return r; }
__device__ __forceinline__ void wg_fence() { asm volatile("wgmma.fence.sync.aligned;" ::: "memory"); }
__device__ __forceinline__ void wg_commit() { asm volatile("wgmma.commit_group.sync.aligned;" ::: "memory"); }
template <int N> __device__ __forceinline__ void wg_wait() { asm volatile("wgmma.wait_group.sync.aligned %0;" ::"n"(N) : "memory"); }
__device__ __forceinline__ void bar_sync(int id, int n) { asm volatile("bar.sync %0, %1;" ::"r"(id), "r"(n) : "memory"); }
__device__ __forceinline__ void bar_arrive(int id, int n) { asm volatile("bar.arrive %0, %1;" ::"r"(id), "r"(n) : "memory"); }
__device__ __forceinline__ void fence_async_smem() { asm volatile("fence.proxy.async.shared::cta;" ::: "memory"); }
__device__ __forceinline__ void fence_async() { asm volatile("fence.proxy.async;" ::: "memory"); }
__device__ __forceinline__ uint64_t mk_desc(uint32_t saddr, uint32_t lbo, uint32_t sbo) {
  return (uint64_t)((saddr & 0x3FFFF) >> 4) | ((uint64_t)(lbo >> 4) << 16) | ((uint64_t)(sbo >> 4) << 32) | (1ull << 62);
}
__device__ __forceinline__ uint32_t pack_bf16(float lo, float hi) {
  uint32_t r; asm("cvt.rn.bf16x2.f32 %0, %1, %2;" : "=r"(r) : "f"(hi), "f"(lo)); return r;
}
__device__ __forceinline__ float bf_lo(uint32_t v) { return __uint_as_float(v << 16); }
__device__ __forceinline__ float bf_hi(uint32_t v) { return __uint_as_float(v & 0xFFFF0000u); }
__device__ __forceinline__ float rbf(float x) { return __bfloat162float(__float2bfloat16_rn(x)); }
__device__ __forceinline__ float ex2(float x) { float r; asm("ex2.approx.ftz.f32 %0, %1;" : "=f"(r) : "f"(x)); return r; }
__device__ __forceinline__ void red_add_v2(float* p, float a, float b) {
  asm volatile("red.global.add.v2.f32 [%0], {%1, %2};" ::"l"(p), "f"(a), "f"(b) : "memory");
}
__device__ __forceinline__ void pdl_wait() { asm volatile("griddepcontrol.wait;" ::: "memory"); }
__device__ __forceinline__ void pdl_launch() { asm volatile("griddepcontrol.launch_dependents;" ::: "memory"); }

__device__ __forceinline__ void wgmma_m64n256k16_ss_tb(float (&d)[128], uint64_t da, uint64_t db, int sc) {
  asm volatile("{\n.reg .pred p;\nsetp.ne.b32 p, %130, 0;\n"
    "wgmma.mma_async.sync.aligned.m64n256k16.f32.bf16.bf16 {%0, %1, %2, %3, %4, %5, %6, %7, %8, %9, %10, %11, %12, %13, %14, %15, %16, %17, %18, %19, %20, %21, %22, %23, %24, %25, %26, %27, %28, %29, %30, %31, %32, %33, %34, %35, %36, %37, %38, %39, %40, %41, %42, %43, %44, %45, %46, %47, %48, %49, %50, %51, %52, %53, %54, %55, %56, %57, %58, %59, %60, %61, %62, %63, %64, %65, %66, %67, %68, %69, %70, %71, %72, %73, %74, %75, %76, %77, %78, %79, %80, %81, %82, %83, %84, %85, %86, %87, %88, %89, %90, %91, %92, %93, %94, %95, %96, %97, %98, %99, %100, %101, %102, %103, %104, %105, %106, %107, %108, %109, %110, %111, %112, %113, %114, %115, %116, %117, %118, %119, %120, %121, %122, %123, %124, %125, %126, %127}, %128, %129, p, 1, 1, 0, 1;\n}\n"
    : "+f"(d[0]), "+f"(d[1]), "+f"(d[2]), "+f"(d[3]), "+f"(d[4]), "+f"(d[5]), "+f"(d[6]), "+f"(d[7]), "+f"(d[8]), "+f"(d[9]), "+f"(d[10]), "+f"(d[11]), "+f"(d[12]), "+f"(d[13]), "+f"(d[14]), "+f"(d[15]), "+f"(d[16]), "+f"(d[17]), "+f"(d[18]), "+f"(d[19]), "+f"(d[20]), "+f"(d[21]), "+f"(d[22]), "+f"(d[23]), "+f"(d[24]), "+f"(d[25]), "+f"(d[26]), "+f"(d[27]), "+f"(d[28]), "+f"(d[29]), "+f"(d[30]), "+f"(d[31]), "+f"(d[32]), "+f"(d[33]), "+f"(d[34]), "+f"(d[35]), "+f"(d[36]), "+f"(d[37]), "+f"(d[38]), "+f"(d[39]), "+f"(d[40]), "+f"(d[41]), "+f"(d[42]), "+f"(d[43]), "+f"(d[44]), "+f"(d[45]), "+f"(d[46]), "+f"(d[47]), "+f"(d[48]), "+f"(d[49]), "+f"(d[50]), "+f"(d[51]), "+f"(d[52]), "+f"(d[53]), "+f"(d[54]), "+f"(d[55]), "+f"(d[56]), "+f"(d[57]), "+f"(d[58]), "+f"(d[59]), "+f"(d[60]), "+f"(d[61]), "+f"(d[62]), "+f"(d[63]), "+f"(d[64]), "+f"(d[65]), "+f"(d[66]), "+f"(d[67]), "+f"(d[68]), "+f"(d[69]), "+f"(d[70]), "+f"(d[71]), "+f"(d[72]), "+f"(d[73]), "+f"(d[74]), "+f"(d[75]), "+f"(d[76]), "+f"(d[77]), "+f"(d[78]), "+f"(d[79]), "+f"(d[80]), "+f"(d[81]), "+f"(d[82]), "+f"(d[83]), "+f"(d[84]), "+f"(d[85]), "+f"(d[86]), "+f"(d[87]), "+f"(d[88]), "+f"(d[89]), "+f"(d[90]), "+f"(d[91]), "+f"(d[92]), "+f"(d[93]), "+f"(d[94]), "+f"(d[95]), "+f"(d[96]), "+f"(d[97]), "+f"(d[98]), "+f"(d[99]), "+f"(d[100]), "+f"(d[101]), "+f"(d[102]), "+f"(d[103]), "+f"(d[104]), "+f"(d[105]), "+f"(d[106]), "+f"(d[107]), "+f"(d[108]), "+f"(d[109]), "+f"(d[110]), "+f"(d[111]), "+f"(d[112]), "+f"(d[113]), "+f"(d[114]), "+f"(d[115]), "+f"(d[116]), "+f"(d[117]), "+f"(d[118]), "+f"(d[119]), "+f"(d[120]), "+f"(d[121]), "+f"(d[122]), "+f"(d[123]), "+f"(d[124]), "+f"(d[125]), "+f"(d[126]), "+f"(d[127])
    : "l"(da), "l"(db), "r"(sc));
}
__device__ __forceinline__ void wgmma_m64n128k16_ss(float (&d)[64], uint64_t da, uint64_t db, int sc) {
  asm volatile("{\n.reg .pred p;\nsetp.ne.b32 p, %66, 0;\n"
    "wgmma.mma_async.sync.aligned.m64n128k16.f32.bf16.bf16 {%0, %1, %2, %3, %4, %5, %6, %7, %8, %9, %10, %11, %12, %13, %14, %15, %16, %17, %18, %19, %20, %21, %22, %23, %24, %25, %26, %27, %28, %29, %30, %31, %32, %33, %34, %35, %36, %37, %38, %39, %40, %41, %42, %43, %44, %45, %46, %47, %48, %49, %50, %51, %52, %53, %54, %55, %56, %57, %58, %59, %60, %61, %62, %63}, %64, %65, p, 1, 1, 0, 0;\n}\n"
    : "+f"(d[0]), "+f"(d[1]), "+f"(d[2]), "+f"(d[3]), "+f"(d[4]), "+f"(d[5]), "+f"(d[6]), "+f"(d[7]), "+f"(d[8]), "+f"(d[9]), "+f"(d[10]), "+f"(d[11]), "+f"(d[12]), "+f"(d[13]), "+f"(d[14]), "+f"(d[15]), "+f"(d[16]), "+f"(d[17]), "+f"(d[18]), "+f"(d[19]), "+f"(d[20]), "+f"(d[21]), "+f"(d[22]), "+f"(d[23]), "+f"(d[24]), "+f"(d[25]), "+f"(d[26]), "+f"(d[27]), "+f"(d[28]), "+f"(d[29]), "+f"(d[30]), "+f"(d[31]), "+f"(d[32]), "+f"(d[33]), "+f"(d[34]), "+f"(d[35]), "+f"(d[36]), "+f"(d[37]), "+f"(d[38]), "+f"(d[39]), "+f"(d[40]), "+f"(d[41]), "+f"(d[42]), "+f"(d[43]), "+f"(d[44]), "+f"(d[45]), "+f"(d[46]), "+f"(d[47]), "+f"(d[48]), "+f"(d[49]), "+f"(d[50]), "+f"(d[51]), "+f"(d[52]), "+f"(d[53]), "+f"(d[54]), "+f"(d[55]), "+f"(d[56]), "+f"(d[57]), "+f"(d[58]), "+f"(d[59]), "+f"(d[60]), "+f"(d[61]), "+f"(d[62]), "+f"(d[63])
    : "l"(da), "l"(db), "r"(sc));
}
__device__ __forceinline__ void wgmma_m64n256k16_rs_tb(float (&d)[128], uint32_t a0, uint32_t a1, uint32_t a2, uint32_t a3, uint64_t db, int sc) {
  asm volatile("{\n.reg .pred p;\nsetp.ne.b32 p, %133, 0;\n"
    "wgmma.mma_async.sync.aligned.m64n256k16.f32.bf16.bf16 {%0, %1, %2, %3, %4, %5, %6, %7, %8, %9, %10, %11, %12, %13, %14, %15, %16, %17, %18, %19, %20, %21, %22, %23, %24, %25, %26, %27, %28, %29, %30, %31, %32, %33, %34, %35, %36, %37, %38, %39, %40, %41, %42, %43, %44, %45, %46, %47, %48, %49, %50, %51, %52, %53, %54, %55, %56, %57, %58, %59, %60, %61, %62, %63, %64, %65, %66, %67, %68, %69, %70, %71, %72, %73, %74, %75, %76, %77, %78, %79, %80, %81, %82, %83, %84, %85, %86, %87, %88, %89, %90, %91, %92, %93, %94, %95, %96, %97, %98, %99, %100, %101, %102, %103, %104, %105, %106, %107, %108, %109, %110, %111, %112, %113, %114, %115, %116, %117, %118, %119, %120, %121, %122, %123, %124, %125, %126, %127}, {%128, %129, %130, %131}, %132, p, 1, 1, 1;\n}\n"
    : "+f"(d[0]), "+f"(d[1]), "+f"(d[2]), "+f"(d[3]), "+f"(d[4]), "+f"(d[5]), "+f"(d[6]), "+f"(d[7]), "+f"(d[8]), "+f"(d[9]), "+f"(d[10]), "+f"(d[11]), "+f"(d[12]), "+f"(d[13]), "+f"(d[14]), "+f"(d[15]), "+f"(d[16]), "+f"(d[17]), "+f"(d[18]), "+f"(d[19]), "+f"(d[20]), "+f"(d[21]), "+f"(d[22]), "+f"(d[23]), "+f"(d[24]), "+f"(d[25]), "+f"(d[26]), "+f"(d[27]), "+f"(d[28]), "+f"(d[29]), "+f"(d[30]), "+f"(d[31]), "+f"(d[32]), "+f"(d[33]), "+f"(d[34]), "+f"(d[35]), "+f"(d[36]), "+f"(d[37]), "+f"(d[38]), "+f"(d[39]), "+f"(d[40]), "+f"(d[41]), "+f"(d[42]), "+f"(d[43]), "+f"(d[44]), "+f"(d[45]), "+f"(d[46]), "+f"(d[47]), "+f"(d[48]), "+f"(d[49]), "+f"(d[50]), "+f"(d[51]), "+f"(d[52]), "+f"(d[53]), "+f"(d[54]), "+f"(d[55]), "+f"(d[56]), "+f"(d[57]), "+f"(d[58]), "+f"(d[59]), "+f"(d[60]), "+f"(d[61]), "+f"(d[62]), "+f"(d[63]), "+f"(d[64]), "+f"(d[65]), "+f"(d[66]), "+f"(d[67]), "+f"(d[68]), "+f"(d[69]), "+f"(d[70]), "+f"(d[71]), "+f"(d[72]), "+f"(d[73]), "+f"(d[74]), "+f"(d[75]), "+f"(d[76]), "+f"(d[77]), "+f"(d[78]), "+f"(d[79]), "+f"(d[80]), "+f"(d[81]), "+f"(d[82]), "+f"(d[83]), "+f"(d[84]), "+f"(d[85]), "+f"(d[86]), "+f"(d[87]), "+f"(d[88]), "+f"(d[89]), "+f"(d[90]), "+f"(d[91]), "+f"(d[92]), "+f"(d[93]), "+f"(d[94]), "+f"(d[95]), "+f"(d[96]), "+f"(d[97]), "+f"(d[98]), "+f"(d[99]), "+f"(d[100]), "+f"(d[101]), "+f"(d[102]), "+f"(d[103]), "+f"(d[104]), "+f"(d[105]), "+f"(d[106]), "+f"(d[107]), "+f"(d[108]), "+f"(d[109]), "+f"(d[110]), "+f"(d[111]), "+f"(d[112]), "+f"(d[113]), "+f"(d[114]), "+f"(d[115]), "+f"(d[116]), "+f"(d[117]), "+f"(d[118]), "+f"(d[119]), "+f"(d[120]), "+f"(d[121]), "+f"(d[122]), "+f"(d[123]), "+f"(d[124]), "+f"(d[125]), "+f"(d[126]), "+f"(d[127])
    : "r"(a0), "r"(a1), "r"(a2), "r"(a3), "l"(db), "r"(sc));
}
__device__ __forceinline__ void wgmma_m64n128k16_ss_tb(float (&d)[64], uint64_t da, uint64_t db, int sc) {
  asm volatile("{\n.reg .pred p;\nsetp.ne.b32 p, %66, 0;\n"
    "wgmma.mma_async.sync.aligned.m64n128k16.f32.bf16.bf16 {%0, %1, %2, %3, %4, %5, %6, %7, %8, %9, %10, %11, %12, %13, %14, %15, %16, %17, %18, %19, %20, %21, %22, %23, %24, %25, %26, %27, %28, %29, %30, %31, %32, %33, %34, %35, %36, %37, %38, %39, %40, %41, %42, %43, %44, %45, %46, %47, %48, %49, %50, %51, %52, %53, %54, %55, %56, %57, %58, %59, %60, %61, %62, %63}, %64, %65, p, 1, 1, 0, 1;\n}\n"
    : "+f"(d[0]), "+f"(d[1]), "+f"(d[2]), "+f"(d[3]), "+f"(d[4]), "+f"(d[5]), "+f"(d[6]), "+f"(d[7]), "+f"(d[8]), "+f"(d[9]), "+f"(d[10]), "+f"(d[11]), "+f"(d[12]), "+f"(d[13]), "+f"(d[14]), "+f"(d[15]), "+f"(d[16]), "+f"(d[17]), "+f"(d[18]), "+f"(d[19]), "+f"(d[20]), "+f"(d[21]), "+f"(d[22]), "+f"(d[23]), "+f"(d[24]), "+f"(d[25]), "+f"(d[26]), "+f"(d[27]), "+f"(d[28]), "+f"(d[29]), "+f"(d[30]), "+f"(d[31]), "+f"(d[32]), "+f"(d[33]), "+f"(d[34]), "+f"(d[35]), "+f"(d[36]), "+f"(d[37]), "+f"(d[38]), "+f"(d[39]), "+f"(d[40]), "+f"(d[41]), "+f"(d[42]), "+f"(d[43]), "+f"(d[44]), "+f"(d[45]), "+f"(d[46]), "+f"(d[47]), "+f"(d[48]), "+f"(d[49]), "+f"(d[50]), "+f"(d[51]), "+f"(d[52]), "+f"(d[53]), "+f"(d[54]), "+f"(d[55]), "+f"(d[56]), "+f"(d[57]), "+f"(d[58]), "+f"(d[59]), "+f"(d[60]), "+f"(d[61]), "+f"(d[62]), "+f"(d[63])
    : "l"(da), "l"(db), "r"(sc));
}
__device__ __forceinline__ void wgmma_m64n128k16_rs_tb(float (&d)[64], uint32_t a0, uint32_t a1, uint32_t a2, uint32_t a3, uint64_t db, int sc) {
  asm volatile("{\n.reg .pred p;\nsetp.ne.b32 p, %69, 0;\n"
    "wgmma.mma_async.sync.aligned.m64n128k16.f32.bf16.bf16 {%0, %1, %2, %3, %4, %5, %6, %7, %8, %9, %10, %11, %12, %13, %14, %15, %16, %17, %18, %19, %20, %21, %22, %23, %24, %25, %26, %27, %28, %29, %30, %31, %32, %33, %34, %35, %36, %37, %38, %39, %40, %41, %42, %43, %44, %45, %46, %47, %48, %49, %50, %51, %52, %53, %54, %55, %56, %57, %58, %59, %60, %61, %62, %63}, {%64, %65, %66, %67}, %68, p, 1, 1, 1;\n}\n"
    : "+f"(d[0]), "+f"(d[1]), "+f"(d[2]), "+f"(d[3]), "+f"(d[4]), "+f"(d[5]), "+f"(d[6]), "+f"(d[7]), "+f"(d[8]), "+f"(d[9]), "+f"(d[10]), "+f"(d[11]), "+f"(d[12]), "+f"(d[13]), "+f"(d[14]), "+f"(d[15]), "+f"(d[16]), "+f"(d[17]), "+f"(d[18]), "+f"(d[19]), "+f"(d[20]), "+f"(d[21]), "+f"(d[22]), "+f"(d[23]), "+f"(d[24]), "+f"(d[25]), "+f"(d[26]), "+f"(d[27]), "+f"(d[28]), "+f"(d[29]), "+f"(d[30]), "+f"(d[31]), "+f"(d[32]), "+f"(d[33]), "+f"(d[34]), "+f"(d[35]), "+f"(d[36]), "+f"(d[37]), "+f"(d[38]), "+f"(d[39]), "+f"(d[40]), "+f"(d[41]), "+f"(d[42]), "+f"(d[43]), "+f"(d[44]), "+f"(d[45]), "+f"(d[46]), "+f"(d[47]), "+f"(d[48]), "+f"(d[49]), "+f"(d[50]), "+f"(d[51]), "+f"(d[52]), "+f"(d[53]), "+f"(d[54]), "+f"(d[55]), "+f"(d[56]), "+f"(d[57]), "+f"(d[58]), "+f"(d[59]), "+f"(d[60]), "+f"(d[61]), "+f"(d[62]), "+f"(d[63])
    : "r"(a0), "r"(a1), "r"(a2), "r"(a3), "l"(db), "r"(sc));
}
__device__ __forceinline__ void wgmma_m64n64k16_ss_tb(float (&d)[32], uint64_t da, uint64_t db, int sc) {
  asm volatile("{\n.reg .pred p;\nsetp.ne.b32 p, %34, 0;\n"
    "wgmma.mma_async.sync.aligned.m64n64k16.f32.bf16.bf16 {%0, %1, %2, %3, %4, %5, %6, %7, %8, %9, %10, %11, %12, %13, %14, %15, %16, %17, %18, %19, %20, %21, %22, %23, %24, %25, %26, %27, %28, %29, %30, %31}, %32, %33, p, 1, 1, 0, 1;\n}\n"
    : "+f"(d[0]), "+f"(d[1]), "+f"(d[2]), "+f"(d[3]), "+f"(d[4]), "+f"(d[5]), "+f"(d[6]), "+f"(d[7]), "+f"(d[8]), "+f"(d[9]), "+f"(d[10]), "+f"(d[11]), "+f"(d[12]), "+f"(d[13]), "+f"(d[14]), "+f"(d[15]), "+f"(d[16]), "+f"(d[17]), "+f"(d[18]), "+f"(d[19]), "+f"(d[20]), "+f"(d[21]), "+f"(d[22]), "+f"(d[23]), "+f"(d[24]), "+f"(d[25]), "+f"(d[26]), "+f"(d[27]), "+f"(d[28]), "+f"(d[29]), "+f"(d[30]), "+f"(d[31])
    : "l"(da), "l"(db), "r"(sc));
}
__device__ __forceinline__ void wgmma_m64n64k16_rs_tb(float (&d)[32], uint32_t a0, uint32_t a1, uint32_t a2, uint32_t a3, uint64_t db, int sc) {
  asm volatile("{\n.reg .pred p;\nsetp.ne.b32 p, %37, 0;\n"
    "wgmma.mma_async.sync.aligned.m64n64k16.f32.bf16.bf16 {%0, %1, %2, %3, %4, %5, %6, %7, %8, %9, %10, %11, %12, %13, %14, %15, %16, %17, %18, %19, %20, %21, %22, %23, %24, %25, %26, %27, %28, %29, %30, %31}, {%32, %33, %34, %35}, %36, p, 1, 1, 1;\n}\n"
    : "+f"(d[0]), "+f"(d[1]), "+f"(d[2]), "+f"(d[3]), "+f"(d[4]), "+f"(d[5]), "+f"(d[6]), "+f"(d[7]), "+f"(d[8]), "+f"(d[9]), "+f"(d[10]), "+f"(d[11]), "+f"(d[12]), "+f"(d[13]), "+f"(d[14]), "+f"(d[15]), "+f"(d[16]), "+f"(d[17]), "+f"(d[18]), "+f"(d[19]), "+f"(d[20]), "+f"(d[21]), "+f"(d[22]), "+f"(d[23]), "+f"(d[24]), "+f"(d[25]), "+f"(d[26]), "+f"(d[27]), "+f"(d[28]), "+f"(d[29]), "+f"(d[30]), "+f"(d[31])
    : "r"(a0), "r"(a1), "r"(a2), "r"(a3), "l"(db), "r"(sc));
}
__device__ __forceinline__ void wgmma_m64n192k16_ss_tb(float (&d)[128], uint64_t da, uint64_t db, int sc) {
  asm volatile("{\n.reg .pred p;\nsetp.ne.b32 p, %98, 0;\n"
    "wgmma.mma_async.sync.aligned.m64n192k16.f32.bf16.bf16 {%0, %1, %2, %3, %4, %5, %6, %7, %8, %9, %10, %11, %12, %13, %14, %15, %16, %17, %18, %19, %20, %21, %22, %23, %24, %25, %26, %27, %28, %29, %30, %31, %32, %33, %34, %35, %36, %37, %38, %39, %40, %41, %42, %43, %44, %45, %46, %47, %48, %49, %50, %51, %52, %53, %54, %55, %56, %57, %58, %59, %60, %61, %62, %63, %64, %65, %66, %67, %68, %69, %70, %71, %72, %73, %74, %75, %76, %77, %78, %79, %80, %81, %82, %83, %84, %85, %86, %87, %88, %89, %90, %91, %92, %93, %94, %95}, %96, %97, p, 1, 1, 0, 1;\n}\n"
    : "+f"(d[0]), "+f"(d[1]), "+f"(d[2]), "+f"(d[3]), "+f"(d[4]), "+f"(d[5]), "+f"(d[6]), "+f"(d[7]), "+f"(d[8]), "+f"(d[9]), "+f"(d[10]), "+f"(d[11]), "+f"(d[12]), "+f"(d[13]), "+f"(d[14]), "+f"(d[15]), "+f"(d[16]), "+f"(d[17]), "+f"(d[18]), "+f"(d[19]), "+f"(d[20]), "+f"(d[21]), "+f"(d[22]), "+f"(d[23]), "+f"(d[24]), "+f"(d[25]), "+f"(d[26]), "+f"(d[27]), "+f"(d[28]), "+f"(d[29]), "+f"(d[30]), "+f"(d[31]), "+f"(d[32]), "+f"(d[33]), "+f"(d[34]), "+f"(d[35]), "+f"(d[36]), "+f"(d[37]), "+f"(d[38]), "+f"(d[39]), "+f"(d[40]), "+f"(d[41]), "+f"(d[42]), "+f"(d[43]), "+f"(d[44]), "+f"(d[45]), "+f"(d[46]), "+f"(d[47]), "+f"(d[48]), "+f"(d[49]), "+f"(d[50]), "+f"(d[51]), "+f"(d[52]), "+f"(d[53]), "+f"(d[54]), "+f"(d[55]), "+f"(d[56]), "+f"(d[57]), "+f"(d[58]), "+f"(d[59]), "+f"(d[60]), "+f"(d[61]), "+f"(d[62]), "+f"(d[63]), "+f"(d[64]), "+f"(d[65]), "+f"(d[66]), "+f"(d[67]), "+f"(d[68]), "+f"(d[69]), "+f"(d[70]), "+f"(d[71]), "+f"(d[72]), "+f"(d[73]), "+f"(d[74]), "+f"(d[75]), "+f"(d[76]), "+f"(d[77]), "+f"(d[78]), "+f"(d[79]), "+f"(d[80]), "+f"(d[81]), "+f"(d[82]), "+f"(d[83]), "+f"(d[84]), "+f"(d[85]), "+f"(d[86]), "+f"(d[87]), "+f"(d[88]), "+f"(d[89]), "+f"(d[90]), "+f"(d[91]), "+f"(d[92]), "+f"(d[93]), "+f"(d[94]), "+f"(d[95])
    : "l"(da), "l"(db), "r"(sc));
}

#define TM(id)
#define GT_MIN(i)
#define GT_MAX(i)

constexpr int NS = 5;
constexpr uint32_t STG = 32768;
constexpr uint32_t SM_Q = 0;
constexpr uint32_t SM_RING = 65536;
constexpr uint32_t SM_BAR = SM_RING + NS * STG;
constexpr uint32_t SM_TOTAL = SM_BAR + 256 + 1024;

struct Ring {
  uint32_t base, full0, empty0, st, ph, nst, stg;
  __device__ __forceinline__ void init(uint32_t sb) { base = sb + SM_RING; full0 = sb + SM_BAR; empty0 = sb + SM_BAR + 64; st = 0; ph = 0; nst = NS; stg = STG; }
  __device__ __forceinline__ uint32_t phase() const { return (ph >> st) & 1; }
  __device__ __forceinline__ uint32_t buf() const { return base + st * stg; }
  __device__ __forceinline__ uint32_t full() const { return full0 + st * 8; }
  __device__ __forceinline__ uint32_t empty() const { return empty0 + st * 8; }
  __device__ __forceinline__ void next() { ph ^= 1u << st; st = (st + 1 >= nst) ? 0 : st + 1; }
  __device__ __forceinline__ void shrink() { nst = NS - 1; if (st >= nst) st = 0; }
  __device__ __forceinline__ uint32_t acquire(uint32_t bytes) {
    mbar_wait(empty(), phase() ^ 1); mbar_expect_tx(full(), bytes); return buf();
  }
  __device__ __forceinline__ uint32_t wait() { mbar_wait(full(), phase()); return buf(); }
};
template <int CL = 2>
__device__ __forceinline__ void ring_release(uint32_t empty_bar, int lane) {
  __syncwarp();
  if (lane < CL) mbar_arrive_remote(empty_bar, (uint32_t)lane);
}

template <int CL>
__device__ __forceinline__ void gemm_k448_n256(Ring& r, float (&acc)[128], int wg, int lane) {
  uint32_t hb = 0, hrel = 0, prel = 0, phrel = 0;
#pragma unroll
  for (int c = 0; c < 7; ++c) {
    if ((c & 1) == 0) { hb = r.wait(); hrel = r.empty(); r.next(); }
    uint32_t wb = r.wait(); uint32_t wrel = r.empty(); r.next();
    uint64_t da = mk_desc(hb + (c & 1) * 16384 + wg * 8192, 16, 1024);
    uint64_t db = mk_desc(wb, 8192, 1024);
    wg_fence();
#pragma unroll
    for (int k = 0; k < 4; ++k) wgmma_m64n256k16_ss_tb(acc, da + k * 2, db + k * 128, (c | k) != 0);
    wg_commit();
    if (c > 0) {
      wg_wait<1>();
      ring_release<CL>(prel, lane);
      if ((c & 1) == 0) ring_release<CL>(phrel, lane);
    }
    prel = wrel; phrel = hrel;
  }
  wg_wait<0>();
  ring_release<CL>(prel, lane); ring_release<CL>(phrel, lane);
}

template <bool RELU>
__device__ __forceinline__ void store_tile_bf16(uint32_t base, const float (&acc)[128], int rloc, int t4) {
  uint32_t row0 = base + rloc * 128, row1 = row0 + 8 * 128;
  uint32_t sw = (uint32_t)(rloc & 7);
#pragma unroll
  for (int j = 0; j < 32; ++j) {
    uint32_t off = (uint32_t)(j >> 3) * 16384 + ((((uint32_t)j & 7) ^ sw) << 4) + t4 * 4;
    float a = acc[4 * j], b = acc[4 * j + 1], c = acc[4 * j + 2], d = acc[4 * j + 3];
    if (RELU) { a = fmaxf(a, 0.f); b = fmaxf(b, 0.f); c = fmaxf(c, 0.f); d = fmaxf(d, 0.f); }
    asm volatile("st.shared.b32 [%0], %1;" ::"r"(row0 + off), "r"(pack_bf16(a, b)) : "memory");
    asm volatile("st.shared.b32 [%0], %1;" ::"r"(row1 + off), "r"(pack_bf16(c, d)) : "memory");
  }
}

template <int NJ, int OFF = 0, int SZ = 64, bool WAIT = true>
__device__ __forceinline__ void red_rows(uint32_t stg, const CUtensorMap* tm, int row0, int col0, const float (&a)[SZ], int sel, int lane) {
  asm volatile("" : "+r"(stg), "+r"(lane));
  if (WAIT) {
    if (lane == 0) asm volatile("cp.async.bulk.wait_group.read 0;" ::: "memory");
    __syncwarp();
  }
  const uint32_t g = lane >> 2, t4 = lane & 3;
  const uint32_t wbase = stg + g * 128 + (t4 & 1) * 8;
#pragma unroll
  for (int j = 0; j < NJ; ++j)
    asm volatile("st.shared.v2.f32 [%0], {%1, %2};" ::"r"(wbase + (j >> 2) * 1024 + ((((j & 3) * 2 + (t4 >> 1)) ^ g) << 4)),
                 "f"(a[OFF + 4 * j + sel]), "f"(a[OFF + 4 * j + sel + 1]) : "memory");
  fence_async_smem();
  __syncwarp();
  if (lane == 0) {
#pragma unroll
    for (int b = 0; b < NJ / 4; ++b)
      asm volatile("cp.reduce.async.bulk.tensor.2d.global.shared::cta.add.tile.bulk_group [%0, {%2, %3}], [%1];"
                   ::"l"(tm), "r"(stg + b * 1024), "r"(col0 + b * 32), "r"(row0) : "memory");
    asm volatile("cp.async.bulk.commit_group;" ::: "memory");
  }
}

template <int NSM, int NRG, int CL>
__device__ __forceinline__ void out_proj(Ring& r, const uint32_t (&ob)[64], uint32_t abase,
                                         const CUtensorMap* tm, int roww, uint32_t stg, int lane) {
  constexpr int NST = (NSM + NRG) / 2;
  uint32_t prel = 0;
  float accA[64], accB[64];
  float(&cur32)[32] = *reinterpret_cast<float(*)[32]>(&accB[0]);
#pragma unroll
  for (int pass = 0; pass < 4; ++pass) {
    float(&cur)[64] = (pass & 1) ? accB : accA;
    float(&prv)[64] = (pass & 1) ? accA : accB;
#pragma unroll
    for (int st = 0; st < NST; ++st) {
      uint32_t wb = r.wait(); uint32_t rel = r.empty(); r.next();
      asm volatile("" : "+r"(abase));
      wg_fence();
#pragma unroll
      for (int cc = 0; cc < 2; ++cc) {
        const int c = 2 * st + cc;
#pragma unroll
        for (int k = 0; k < 4; ++k) {
          const int sc = (c | k) != 0;
          if (pass < 3) {
            uint64_t db = mk_desc(wb + cc * 16384 + k * 2048, 8192, 1024);
            if (c < NSM) wgmma_m64n128k16_ss_tb(cur, mk_desc(abase + c * 16384 + k * 32, 16, 1024), db, sc);
            else { const int o = (c - NSM) * 16 + 4 * k; wgmma_m64n128k16_rs_tb(cur, ob[o], ob[o + 1], ob[o + 2], ob[o + 3], db, sc); }
          } else {
            uint64_t db = mk_desc(wb + cc * 8192 + k * 2048, 8192, 1024);
            if (c < NSM) wgmma_m64n64k16_ss_tb(cur32, mk_desc(abase + c * 16384 + k * 32, 16, 1024), db, sc);
            else { const int o = (c - NSM) * 16 + 4 * k; wgmma_m64n64k16_rs_tb(cur32, ob[o], ob[o + 1], ob[o + 2], ob[o + 3], db, sc); }
          }
        }
      }
      wg_commit();
      if (pass | st) { wg_wait<1>(); ring_release<CL>(prel, lane); }
      prel = rel;
      if (pass > 0) {
        if (st == 0) red_rows<16>(stg, tm, roww, (pass - 1) * 128, prv, 0, lane);
        if (st == NST / 2) red_rows<16>(stg, tm, roww + 8, (pass - 1) * 128, prv, 2, lane);
      }
    }
  }
  wg_wait<0>(); ring_release<CL>(prel, lane);
  red_rows<8>(stg, tm, roww, 384, accB, 0, lane);
  red_rows<8>(stg, tm, roww + 8, 384, accB, 2, lane);
  if (lane == 0) asm volatile("cp.async.bulk.wait_group 0;" ::: "memory");
}
template <int CL>
__device__ __forceinline__ void out_proj_loads(Ring& r, const CUtensorMap* tm, int krow0, int nch, uint32_t rank) {
  r.shrink();
  constexpr uint16_t MASK = (1 << CL) - 1;
  for (int pass = 0; pass < 4; ++pass)
    for (int st = 0; st < nch / 2; ++st) {
      if (pass < 3) {
        uint32_t b = r.acquire(32768);
        for (int x = 0; x < 4 / CL; ++x) {
          const int bx = rank * (4 / CL) + x;
          tma_load_mc(b + bx * 8192, tm, pass * 128 + (bx & 1) * 64, krow0 + (2 * st + (bx >> 1)) * 64, r.full(), MASK);
        }
      } else {
        uint32_t b = r.acquire(16384);
        if (CL == 1) { for (int x = 0; x < 2; ++x) tma_load_mc(b + x * 8192, tm, 384, krow0 + (2 * st + x) * 64, r.full(), MASK); }
        else if (rank < 2) tma_load_mc(b + rank * 8192, tm, 384, krow0 + (2 * st + rank) * 64, r.full(), MASK);
      }
      r.next();
    }
}

#define ACL 2
__global__ void __cluster_dims__(ACL, 1, 1) __launch_bounds__(384, 1)
attn_kernel(const __grid_constant__ CUtensorMap tm_h, const __grid_constant__ CUtensorMap tm_wq,
            const __grid_constant__ CUtensorMap tm_k, const __grid_constant__ CUtensorMap tm_v,
            const __grid_constant__ CUtensorMap tm_wo, const __grid_constant__ CUtensorMap tm_oA,
            const __grid_constant__ CUtensorMap tm_oAs, const __grid_constant__ CUtensorMap tm_acc) {
  extern __shared__ uint8_t smem_raw[];
  const uint32_t sb = (smem_u32(smem_raw) + 1023) & ~1023u;
  const int tid = threadIdx.x, wg = tid >> 7, lane = tid & 31;
  const int qt = blockIdx.x, kvh = blockIdx.y;
  const uint32_t rank = cluster_rank();
  Ring r; r.init(sb);
  const uint32_t bar_oA = sb + SM_BAR + 128, bar_oAf = sb + SM_BAR + 136;
  if (tid == 0) {
    for (int i = 0; i < NS; ++i) { mbar_init(r.full0 + 8 * i, 1); mbar_init(r.empty0 + 8 * i, 8 * ACL); }
    mbar_init(bar_oA, 256); mbar_init(bar_oAf, 1);
    asm volatile("fence.mbarrier_init.release.cluster;" ::: "memory");
  }
  cluster_sync_all();
  pdl_wait();
  GT_MIN(4);

  if (wg == 2) {
    asm volatile("setmaxnreg.dec.sync.aligned.u32 24;");
    if (tid == 256) {
      const int krow0 = kvh * SKV + (SKV - WIN);
      for (int hh = 0; hh < 2; ++hh) {
        const int head = kvh * 2 + hh;
        for (int p = 0; p < 4; ++p) {
          int nc = (p < 3) ? 2 : 1;
          uint32_t b = r.acquire(nc * 16384);
          for (int c = 0; c < nc; ++c) tma_load(b + c * 16384, &tm_h, (2 * p + c) * 64, qt * 128, r.full());
          r.next();
          for (int c = 0; c < nc; ++c) {
            b = r.acquire(32768);
            for (int x = 0; x < 4 / ACL; ++x) {
              int bx = rank * 2 + x;
              tma_load_mc(b + bx * 8192, &tm_wq, head * 256 + bx * 64, (2 * p + c) * 64, r.full(), (1 << ACL) - 1);
            }
            r.next();
          }
        }
        for (int t = 0; t < 4; ++t) {
          for (int hf = 0; hf < 2; ++hf) {
            uint32_t b = r.acquire(32768);
            for (int x = 0; x < 2 / ACL; ++x)
              tma_load_mc(b + (rank + x) * 16384, &tm_k, (2 * hf + rank + x) * 64, krow0 + t * 128, r.full(), (1 << ACL) - 1);
            r.next();
          }
          for (int hf = 0; hf < 2; ++hf) {
            uint32_t b = r.acquire(32768);
            for (int x = 0; x < 4 / ACL; ++x) {
              int bx = rank * 2 + x;
              tma_load_mc(b + bx * 8192, &tm_v, bx * 64, krow0 + t * 128 + hf * 64, r.full(), (1 << ACL) - 1);
            }
            r.next();
          }
        }
      }
      mbar_wait(bar_oA, 0);
      mbar_expect_tx(bar_oAf, 65536);
      for (int c = 0; c < 4; ++c) tma_load(sb + SM_Q + c * 16384, &tm_oA, c * 64, kvh * SEQ + qt * 128, bar_oAf);
      out_proj_loads<ACL>(r, &tm_wo, kvh * 512, 8, rank);
    }
  } else {
    asm volatile("setmaxnreg.inc.sync.aligned.u32 240;");
    const int warp = (tid >> 5) & 3, g = lane >> 2, t4 = lane & 3;
    const int rloc = wg * 64 + warp * 16 + g;
    uint32_t ob[64];
    float acc[128];
    const float CS = 1.4426950408889634f * 0.0625f;
    TM(0);
#pragma unroll 1
    for (int hh = 0; hh < 2; ++hh) {
      gemm_k448_n256<ACL>(r, acc, wg, lane);
      TM(1);
      if (hh == 1) {
        if ((tid & 127) == 0) asm volatile("cp.async.bulk.wait_group.read 0;" ::: "memory");
        bar_sync(1 + wg, 128);
      }
      store_tile_bf16<false>(sb + SM_Q, acc, rloc, t4);
      fence_async_smem();
      bar_sync(1 + wg, 128);
      float m0 = -INFINITY, m1 = -INFINITY, l0 = 0.f, l1 = 0.f;
      const uint32_t qa0 = sb + SM_Q + wg * 8192;
      if (wg == 1) bar_arrive(3, 256);
      TM(2);
      bar_sync(3 + wg, 256);
#pragma unroll 1
      for (int t = 0; t < 4; ++t) {
        float s[64];
        TM(3);
        {
          uint32_t qa = qa0; asm volatile("" : "+r"(qa));
          uint32_t ka = r.wait(); uint32_t rel0 = r.empty(); r.next();
          wg_fence();
#pragma unroll
          for (int k = 0; k < 8; ++k)
            wgmma_m64n128k16_ss(s, mk_desc(qa + (k >> 2) * 16384 + (k & 3) * 32, 16, 1024),
                                mk_desc(ka + (k >> 2) * 16384 + (k & 3) * 32, 16, 1024), k != 0);
          wg_commit();
          uint32_t kb = r.wait(); uint32_t rel1 = r.empty(); r.next();
          wg_fence();
#pragma unroll
          for (int k = 0; k < 8; ++k)
            wgmma_m64n128k16_ss(s, mk_desc(qa + (2 + (k >> 2)) * 16384 + (k & 3) * 32, 16, 1024),
                                mk_desc(kb + (k >> 2) * 16384 + (k & 3) * 32, 16, 1024), 1);
          wg_commit();
          bar_arrive(4 - wg, 256);
          wg_wait<1>(); ring_release<ACL>(rel0, lane);
          wg_wait<0>(); ring_release<ACL>(rel1, lane);
        }
        TM(4);
        float mx0 = m0, mx1 = m1;
#pragma unroll
        for (int j = 0; j < 16; ++j) {
          uint32_t a = pack_bf16(s[4 * j], s[4 * j + 1]), b = pack_bf16(s[4 * j + 2], s[4 * j + 3]);
          s[4 * j] = bf_lo(a); s[4 * j + 1] = bf_hi(a); s[4 * j + 2] = bf_lo(b); s[4 * j + 3] = bf_hi(b);
          mx0 = fmaxf(mx0, fmaxf(s[4 * j], s[4 * j + 1])); mx1 = fmaxf(mx1, fmaxf(s[4 * j + 2], s[4 * j + 3]));
        }
        mx0 = fmaxf(mx0, __shfl_xor_sync(0xffffffffu, mx0, 1)); mx0 = fmaxf(mx0, __shfl_xor_sync(0xffffffffu, mx0, 2));
        mx1 = fmaxf(mx1, __shfl_xor_sync(0xffffffffu, mx1, 1)); mx1 = fmaxf(mx1, __shfl_xor_sync(0xffffffffu, mx1, 2));
        const float c0 = ex2((m0 - mx0) * CS), c1 = ex2((m1 - mx1) * CS);
        m0 = mx0; m1 = mx1;
        const float nb0 = -mx0 * CS, nb1 = -mx1 * CS;
        float ps0 = 0.f, ps1 = 0.f;
        uint32_t pa[32];
#pragma unroll
        for (int j = 0; j < 16; ++j) {
          float e0 = ex2(fmaf(s[4 * j], CS, nb0)), e1 = ex2(fmaf(s[4 * j + 1], CS, nb0));
          float e2 = ex2(fmaf(s[4 * j + 2], CS, nb1)), e3 = ex2(fmaf(s[4 * j + 3], CS, nb1));
          ps0 += e0 + e1; ps1 += e2 + e3;
          pa[2 * j] = pack_bf16(e0, e1); pa[2 * j + 1] = pack_bf16(e2, e3);
        }
        l0 = l0 * c0 + ps0; l1 = l1 * c1 + ps1;
        if (t > 0) {
#pragma unroll
          for (int j = 0; j < 32; ++j) { acc[4 * j] *= c0; acc[4 * j + 1] *= c0; acc[4 * j + 2] *= c1; acc[4 * j + 3] *= c1; }
        }
#pragma unroll
        for (int j = 0; j < 32; ++j) asm volatile("" : "+r"(pa[j]));
#pragma unroll
        for (int j = 0; j < 128; ++j) asm volatile("" : "+f"(acc[j]));
        asm volatile("" : "+f"(l0), "+f"(l1));
        TM(5);
        bar_sync(3 + wg, 256);
        TM(6);
        {
          uint32_t va = r.wait(); uint32_t rel0 = r.empty(); r.next();
          wg_fence();
#pragma unroll
          for (int k = 0; k < 4; ++k)
            wgmma_m64n256k16_rs_tb(acc, pa[4 * k], pa[4 * k + 1], pa[4 * k + 2], pa[4 * k + 3],
                                   mk_desc(va + k * 2048, 8192, 1024), (t | k) != 0);
          wg_commit();
          uint32_t vb = r.wait(); uint32_t rel1 = r.empty(); r.next();
          wg_fence();
#pragma unroll
          for (int k = 0; k < 4; ++k)
            wgmma_m64n256k16_rs_tb(acc, pa[16 + 4 * k], pa[16 + 4 * k + 1], pa[16 + 4 * k + 2], pa[16 + 4 * k + 3],
                                   mk_desc(vb + k * 2048, 8192, 1024), 1);
          wg_commit();
          if (t == 3 && wg == 0) bar_arrive(4, 256);
          wg_wait<1>(); ring_release<ACL>(rel0, lane);
          wg_wait<0>(); ring_release<ACL>(rel1, lane);
        }
      }
      TM(7);
      l0 += __shfl_xor_sync(0xffffffffu, l0, 1); l0 += __shfl_xor_sync(0xffffffffu, l0, 2);
      l1 += __shfl_xor_sync(0xffffffffu, l1, 1); l1 += __shfl_xor_sync(0xffffffffu, l1, 2);
      const float i0 = 1.f / l0, i1 = 1.f / l1;
#pragma unroll
      for (int j = 0; j < 32; ++j) {
        ob[2 * j] = pack_bf16(acc[4 * j] * i0, acc[4 * j + 1] * i0);
        ob[2 * j + 1] = pack_bf16(acc[4 * j + 2] * i1, acc[4 * j + 3] * i1);
      }
      if (hh == 0) {
        uint32_t row0 = sb + SM_Q + rloc * 128, row1 = row0 + 8 * 128;
        uint32_t sw = (uint32_t)(rloc & 7);
#pragma unroll
        for (int j = 0; j < 32; ++j) {
          uint32_t off = (uint32_t)(j >> 3) * 16384 + ((((uint32_t)j & 7) ^ sw) << 4) + t4 * 4;
          asm volatile("st.shared.b32 [%0], %1;" ::"r"(row0 + off), "r"(ob[2 * j]) : "memory");
          asm volatile("st.shared.b32 [%0], %1;" ::"r"(row1 + off), "r"(ob[2 * j + 1]) : "memory");
        }
        fence_async_smem();
        bar_sync(1 + wg, 128);
        if ((tid & 127) == 0) {
          for (int c = 0; c < 4; ++c)
            asm volatile("cp.async.bulk.tensor.2d.global.shared::cta.bulk_group [%0, {%2, %3}], [%1];"
                         ::"l"(&tm_oAs), "r"(sb + SM_Q + c * 16384 + wg * 8192), "r"(c * 64), "r"(kvh * SEQ + qt * 128 + wg * 64) : "memory");
          asm volatile("cp.async.bulk.commit_group;" ::: "memory");
        }
      }
    }
    if ((tid & 127) == 0) asm volatile("cp.async.bulk.wait_group 0;" ::: "memory");
    mbar_arrive(bar_oA);
    mbar_wait(bar_oAf, 0);
    TM(8);
    r.shrink();
    out_proj<4, 4, ACL>(r, ob, sb + SM_Q + wg * 8192, &tm_acc, qt * 128 + wg * 64 + warp * 16,
                   sb + SM_RING + (NS - 1) * STG + (wg * 4 + warp) * 4096, lane);
    TM(9);
  }
  cluster_sync_all();
  GT_MAX(5);
}

constexpr uint32_t F_STG = 57344, F_A = 0, F_RING = 57344, F_BAR = F_RING + 3 * F_STG, F_TOTAL = F_BAR + 256 + 1024;

template <int WG>
__device__ __forceinline__ void ffn_gemm(Ring& r, float (&acc)[128], uint32_t abase, int lane) {
  uint32_t prel = 0;
#pragma unroll
  for (int c = 0; c < 7; ++c) {
    uint32_t wb = r.wait(); uint32_t wrel = r.empty(); r.next();
    uint64_t da = mk_desc(abase + c * 8192, 16, 1024);
    uint64_t db = mk_desc(wb + WG * 32768, 8192, 1024);
    wg_fence();
#pragma unroll
    for (int k = 0; k < 4; ++k) {
      if (WG == 0) wgmma_m64n256k16_ss_tb(acc, da + k * 2, db + k * 128, (c | k) != 0);
      else wgmma_m64n192k16_ss_tb(acc, da + k * 2, db + k * 128, (c | k) != 0);
    }
    wg_commit();
    if (c > 0) { wg_wait<1>(); ring_release<2>(prel, lane); }
    prel = wrel;
  }
  wg_wait<0>();
  ring_release<2>(prel, lane);
}

template <int WG>
__device__ __forceinline__ void ffn_consumer(Ring& r, uint32_t sb, uint32_t bar_a, int rt, int sl, int warp, int lane, const CUtensorMap* tm,
                                             __nv_bfloat16* __restrict__ out) {
  const int g = lane >> 2, t4 = lane & 3, row = warp * 16 + g;
  float acc[128];
  TM(20);
  mbar_wait(bar_a, 0);
  TM(21);
  ffn_gemm<WG>(r, acc, sb + F_A, lane);
  TM(22);
  bar_sync(5, 256);
  {
    uint32_t row0 = sb + F_A + WG * 32768 + row * 128, row1 = row0 + 8 * 128;
    uint32_t sw = (uint32_t)(row & 7);
#pragma unroll
    for (int j = 0; j < (WG == 0 ? 32 : 24); ++j) {
      uint32_t off = (uint32_t)(j >> 3) * 8192 + ((((uint32_t)j & 7) ^ sw) << 4) + t4 * 4;
      asm volatile("st.shared.b32 [%0], %1;" ::"r"(row0 + off), "r"(pack_bf16(fmaxf(acc[4 * j], 0.f), fmaxf(acc[4 * j + 1], 0.f))) : "memory");
      asm volatile("st.shared.b32 [%0], %1;" ::"r"(row1 + off), "r"(pack_bf16(fmaxf(acc[4 * j + 2], 0.f), fmaxf(acc[4 * j + 3], 0.f))) : "memory");
    }
  }
  fence_async_smem();
  bar_sync(5, 256);
  TM(23);
  ffn_gemm<WG>(r, acc, sb + F_A, lane);
  TM(24);
  bar_sync(5, 256);
  const int r0 = rt * 64 + warp * 16, c0 = WG * 256;
  const uint32_t stg = sb + (WG * 4 + warp) * 16384;
  red_rows<16, 0, 128, false>(stg, tm, r0, c0, acc, 0, lane);
  red_rows<16, 0, 128, false>(stg + 4096, tm, r0 + 8, c0, acc, 2, lane);
  if (WG == 0) {
    red_rows<16, 64, 128, false>(stg + 8192, tm, r0, c0 + 128, acc, 0, lane);
    red_rows<16, 64, 128, false>(stg + 12288, tm, r0 + 8, c0 + 128, acc, 2, lane);
  } else {
    red_rows<8, 64, 128, false>(stg + 8192, tm, r0, c0 + 128, acc, 0, lane);
    red_rows<8, 64, 128, false>(stg + 12288, tm, r0 + 8, c0 + 128, acc, 2, lane);
  }
  if (lane == 0) asm volatile("cp.async.bulk.wait_group 0;" ::: "memory");
  TM(25);
  __syncwarp();
  fence_async();
  __threadfence();
  bar_sync(5, 256);
  if (WG == 0 && warp == 0 && lane == 0) {
    atomicAdd(&g_cnt[rt], 1u);
    for (int it = 0; it < (1 << 24); ++it) {
      unsigned int f;
      asm volatile("ld.acquire.gpu.global.u32 %0, [%1];" : "=r"(f) : "l"(&g_cnt[rt]) : "memory");
      if (f >= 4u) break;
    }
  }
  bar_sync(5, 256);
  {
    const int t = WG * 128 + warp * 32 + lane;
    const size_t base = ((size_t)rt * 64 + sl * 16) * DM;
    float4 a[7]; uint2 u[7];
#pragma unroll
    for (int j = 0; j < 7; ++j) {
      a[j] = __ldcg(reinterpret_cast<const float4*>(g_acc2 + base) + t + j * 256);
      u[j] = __ldcg(reinterpret_cast<const uint2*>(g_x1 + base) + t + j * 256);
    }
#pragma unroll
    for (int j = 0; j < 7; ++j) {
      const int i = t + j * 256, col = (i * 4) % DM;
      float4 gb = *reinterpret_cast<const float4*>(g_mod + 5 * DM + col);
      uint2 o;
      o.x = pack_bf16(bf_lo(u[j].x) + rbf(gb.x * rbf(a[j].x)), bf_hi(u[j].x) + rbf(gb.y * rbf(a[j].y)));
      o.y = pack_bf16(bf_lo(u[j].y) + rbf(gb.z * rbf(a[j].z)), bf_hi(u[j].y) + rbf(gb.w * rbf(a[j].w)));
      reinterpret_cast<uint2*>(out + base)[i] = o;
    }
  }
}

__global__ void __cluster_dims__(2, 1, 1) __launch_bounds__(384, 1)
ffn_kernel(const __grid_constant__ CUtensorMap tm_h2, const __grid_constant__ CUtensorMap tm_w1,
           const __grid_constant__ CUtensorMap tm_w2, const __grid_constant__ CUtensorMap tm_acc,
           __nv_bfloat16* __restrict__ out) {
  extern __shared__ uint8_t smem_raw[];
  const uint32_t sb = (smem_u32(smem_raw) + 1023) & ~1023u;
  const int tid = threadIdx.x, wg = tid >> 7, lane = tid & 31;
  const int rt = blockIdx.x, sl = blockIdx.y;
  const uint32_t rank = cluster_rank();
  Ring r; r.base = sb + F_RING; r.full0 = sb + F_BAR; r.empty0 = sb + F_BAR + 64; r.st = 0; r.ph = 0; r.nst = 3; r.stg = F_STG;
  const uint32_t bar_a = sb + F_BAR + 128;
  if (tid == 0) {
    for (int i = 0; i < 3; ++i) { mbar_init(r.full0 + 8 * i, 1); mbar_init(r.empty0 + 8 * i, 16); }
    mbar_init(bar_a, 1);
    asm volatile("fence.mbarrier_init.release.cluster;" ::: "memory");
  }
  cluster_sync_all();
  if (wg == 2) {
    asm volatile("setmaxnreg.dec.sync.aligned.u32 24;");
    if (tid == 256) {
      const int b0 = rank ? 4 : 0, b1 = rank ? 7 : 4;
      pdl_wait();
      mbar_expect_tx(bar_a, 57344);
      for (int k = 0; k < 7; ++k) tma_load(sb + F_A + k * 8192, &tm_h2, k * 64, rt * 64, bar_a);
      for (int c = 0; c < 14; ++c) {
        uint32_t b = r.acquire(F_STG);
        for (int bx = b0; bx < b1; ++bx) {
          if (c < 7) tma_load_mc(b + bx * 8192, &tm_w1, sl * 448 + bx * 64, c * 64, r.full(), 3);
          else tma_load_mc(b + bx * 8192, &tm_w2, bx * 64, sl * 448 + (c - 7) * 64, r.full(), 3);
        }
        r.next();
      }
    }
  } else {
    asm volatile("setmaxnreg.inc.sync.aligned.u32 240;");
    pdl_wait();
    GT_MIN(8);
    const int warp = (tid >> 5) & 3;
    if (wg == 0) ffn_consumer<0>(r, sb, bar_a, rt, sl, warp, lane, &tm_acc, out);
    else ffn_consumer<1>(r, sb, bar_a, rt, sl, warp, lane, &tm_acc, out);
  }
  cluster_sync_all();
  GT_MAX(9);
}

__global__ void __launch_bounds__(512) mod_kernel(const __nv_bfloat16* __restrict__ c, const __nv_bfloat16* __restrict__ wm) {
  __shared__ float red[32][33];
  const int tid = threadIdx.x;
  pdl_launch();
  GT_MIN(0);
  if (blockIdx.x < 84) {
    const int cl = tid & 15, kg = tid >> 4;
    const int col = blockIdx.x * 32 + cl * 2;
    uint32_t v[14];
#pragma unroll
    for (int i = 0; i < 14; ++i) v[i] = *reinterpret_cast<const uint32_t*>(wm + (size_t)(kg * 14 + i) * (6 * DM) + col);
    float a0 = 0.f, a1 = 0.f;
#pragma unroll
    for (int i = 0; i < 14; ++i) {
      float cv = __bfloat162float(c[kg * 14 + i]);
      float sv = rbf(cv / (1.f + __expf(-cv)));
      a0 = fmaf(sv, bf_lo(v[i]), a0); a1 = fmaf(sv, bf_hi(v[i]), a1);
    }
    red[kg][cl * 2] = a0; red[kg][cl * 2 + 1] = a1;
    __syncthreads();
    if (tid < 32) {
      float s = 0.f;
#pragma unroll
      for (int i = 0; i < 32; ++i) s += red[i][tid];
      g_mod[blockIdx.x * 32 + tid] = rbf(s);
    }
  }
  if (blockIdx.x < 84) GT_MAX(1); else GT_MAX(13);
}

__device__ __forceinline__ void ln_row(const float (&x)[14], const float* __restrict__ shift, const float* __restrict__ scale,
                                       __nv_bfloat16* __restrict__ out, int lane) {
  float2 sc[7], sh[7];
#pragma unroll
  for (int i = 0; i < 7; ++i) {
    sc[i] = *reinterpret_cast<const float2*>(scale + i * 64 + lane * 2);
    sh[i] = *reinterpret_cast<const float2*>(shift + i * 64 + lane * 2);
  }
  float s = 0.f;
#pragma unroll
  for (int i = 0; i < 14; ++i) s += x[i];
#pragma unroll
  for (int o = 16; o; o >>= 1) s += __shfl_xor_sync(0xffffffffu, s, o);
  const float mean = s * (1.f / DM);
  float q = 0.f;
#pragma unroll
  for (int i = 0; i < 14; ++i) { float d = x[i] - mean; q = fmaf(d, d, q); }
#pragma unroll
  for (int o = 16; o; o >>= 1) q += __shfl_xor_sync(0xffffffffu, q, o);
  const float mb = rbf(mean), vb = rbf(q * (1.f / DM));
  const float den = rbf(sqrtf(rbf(vb + 1e-5f)));
#pragma unroll
  for (int i = 0; i < 7; ++i) {
    int col = i * 64 + lane * 2;
    float y0 = rbf(rbf(x[2 * i] - mb) / den), y1 = rbf(rbf(x[2 * i + 1] - mb) / den);
    y0 = rbf(y0 * rbf(1.f + sc[i].x)); y1 = rbf(y1 * rbf(1.f + sc[i].y));
    *reinterpret_cast<uint32_t*>(out + col) = pack_bf16(y0 + sh[i].x, y1 + sh[i].y);
  }
}

__global__ void __launch_bounds__(256) ln1_kernel(const __nv_bfloat16* __restrict__ x) {
  const int lane = threadIdx.x & 31, row = blockIdx.x * 8 + (threadIdx.x >> 5);
  float v[14];
#pragma unroll
  for (int i = 0; i < 7; ++i) {
    uint32_t u = *reinterpret_cast<const uint32_t*>(x + (size_t)row * DM + i * 64 + lane * 2);
    v[2 * i] = bf_lo(u); v[2 * i + 1] = bf_hi(u);
  }
  if (blockIdx.x == 0 && threadIdx.x < 64) g_cnt[threadIdx.x] = 0;
  {
    float4 z = make_float4(0.f, 0.f, 0.f, 0.f);
    const int base = blockIdx.x * (8 * DM / 4);
    for (int i = threadIdx.x; i < 8 * DM / 4; i += 256) {
      reinterpret_cast<float4*>(g_acc1)[base + i] = z; reinterpret_cast<float4*>(g_acc2)[base + i] = z;
    }
  }
  pdl_wait();
  GT_MIN(2);
  ln_row(v, g_mod + 0 * DM, g_mod + 1 * DM, g_h + (size_t)row * DM, lane);
  GT_MAX(3);
  pdl_launch();
}

__global__ void __launch_bounds__(256) ln2_kernel(const __nv_bfloat16* __restrict__ x) {
  const int lane = threadIdx.x & 31, row = blockIdx.x * 8 + (threadIdx.x >> 5);
  float v[14];
  uint32_t xu[7];
#pragma unroll
  for (int i = 0; i < 7; ++i) xu[i] = *reinterpret_cast<const uint32_t*>(x + (size_t)row * DM + i * 64 + lane * 2);
  pdl_wait();
  GT_MIN(6);
  float2 av[7], gv[7];
#pragma unroll
  for (int i = 0; i < 7; ++i) {
    av[i] = *reinterpret_cast<const float2*>(g_acc1 + (size_t)row * DM + i * 64 + lane * 2);
    gv[i] = *reinterpret_cast<const float2*>(g_mod + 2 * DM + i * 64 + lane * 2);
  }
#pragma unroll
  for (int i = 0; i < 7; ++i) {
    int col = i * 64 + lane * 2;
    uint32_t u = xu[i];
    float t0 = rbf(gv[i].x * rbf(av[i].x)), t1 = rbf(gv[i].y * rbf(av[i].y));
    v[2 * i] = rbf(bf_lo(u) + t0); v[2 * i + 1] = rbf(bf_hi(u) + t1);
    *reinterpret_cast<uint32_t*>(g_x1 + (size_t)row * DM + col) = pack_bf16(v[2 * i], v[2 * i + 1]);
  }
  ln_row(v, g_mod + 3 * DM, g_mod + 4 * DM, g_h2 + (size_t)row * DM, lane);
  GT_MAX(7);
  pdl_launch();
}

__global__ void __launch_bounds__(256) final_kernel(__nv_bfloat16* __restrict__ out) {
  const int i = blockIdx.x * 256 + threadIdx.x;
  const int col = (i * 4) % DM;
  pdl_wait();
  GT_MIN(10);
  float4 a = reinterpret_cast<const float4*>(g_acc2)[i];
  uint2 u = reinterpret_cast<const uint2*>(g_x1)[i];
  float4 gb = *reinterpret_cast<const float4*>(g_mod + 5 * DM + col);
  uint2 o;
  o.x = pack_bf16(bf_lo(u.x) + rbf(gb.x * rbf(a.x)), bf_hi(u.x) + rbf(gb.y * rbf(a.y)));
  o.y = pack_bf16(bf_lo(u.y) + rbf(gb.z * rbf(a.z)), bf_hi(u.y) + rbf(gb.w * rbf(a.w)));
  reinterpret_cast<uint2*>(out)[i] = o;
  GT_MAX(11);
}

typedef CUresult (*EncodeFn)(CUtensorMap*, CUtensorMapDataType, cuuint32_t, void*, const cuuint64_t*, const cuuint64_t*,
                             const cuuint32_t*, const cuuint32_t*, CUtensorMapInterleave, CUtensorMapSwizzle,
                             CUtensorMapL2promotion, CUtensorMapFloatOOBfill);

static CUtensorMap make_map(EncodeFn enc, const void* ptr, uint64_t cols, uint64_t rows, uint32_t bx, uint32_t by,
                            bool f32 = false) {
  CUtensorMap m;
  cuuint64_t dims[2] = {cols, rows};
  cuuint64_t strides[1] = {cols * (f32 ? 4 : 2)};
  cuuint32_t box[2] = {bx, by};
  cuuint32_t es[2] = {1, 1};
  enc(&m, f32 ? CU_TENSOR_MAP_DATA_TYPE_FLOAT32 : CU_TENSOR_MAP_DATA_TYPE_BFLOAT16, 2, const_cast<void*>(ptr), dims, strides, box, es, CU_TENSOR_MAP_INTERLEAVE_NONE,
      CU_TENSOR_MAP_SWIZZLE_128B, CU_TENSOR_MAP_L2_PROMOTION_L2_256B, CU_TENSOR_MAP_FLOAT_OOB_FILL_NONE);
  return m;
}

template <typename... Args>
static void launch(void (*k)(Args...), dim3 grid, dim3 block, size_t smem, bool pdl, Args... args) {
  cudaLaunchConfig_t cfg = {};
  cfg.gridDim = grid; cfg.blockDim = block; cfg.dynamicSmemBytes = smem; cfg.stream = cudaStreamPerThread;
  cudaLaunchAttribute at[1];
  at[0].id = cudaLaunchAttributeProgrammaticStreamSerialization; at[0].val.programmaticStreamSerializationAllowed = 1;
  cfg.attrs = at; cfg.numAttrs = pdl ? 1 : 0;
  cudaLaunchKernelEx(&cfg, k, args...);
}

extern "C" void kernel_launch(void* const* d_in, const int* in_sizes, int n_in, void* d_out, int out_size) {
  const __nv_bfloat16* x = (const __nv_bfloat16*)d_in[0];
  const void* kc = d_in[1]; const void* vc = d_in[2]; const void* wq = d_in[3]; const void* wo = d_in[4];
  const void* w1 = d_in[6]; const void* w2 = d_in[7];
  const __nv_bfloat16* c = (const __nv_bfloat16*)d_in[8];
  const __nv_bfloat16* wm = (const __nv_bfloat16*)d_in[9];

  void* fn = nullptr; cudaDriverEntryPointQueryResult qr;
  cudaGetDriverEntryPoint("cuTensorMapEncodeTiled", &fn, cudaEnableDefault, &qr);
  EncodeFn enc = (EncodeFn)fn;
  void *p_h, *p_oA, *p_h2, *p_a1, *p_a2;
  cudaGetSymbolAddress(&p_a1, g_acc1); cudaGetSymbolAddress(&p_a2, g_acc2);
  cudaGetSymbolAddress(&p_h, g_h); cudaGetSymbolAddress(&p_oA, g_oA); cudaGetSymbolAddress(&p_h2, g_h2);
  CUtensorMap tm_h = make_map(enc, p_h, DM, SEQ, 64, 128);
  CUtensorMap tm_wq = make_map(enc, wq, 4096, DM, 64, 64);
  CUtensorMap tm_k = make_map(enc, kc, DH, HKV * SKV, 64, 128);
  CUtensorMap tm_v = make_map(enc, vc, DH, HKV * SKV, 64, 64);
  CUtensorMap tm_wo = make_map(enc, wo, DM, 4096, 64, 64);
  CUtensorMap tm_oA = make_map(enc, p_oA, DH, HKV * SEQ, 64, 128);
  CUtensorMap tm_oAs = make_map(enc, p_oA, DH, HKV * SEQ, 64, 64);
  CUtensorMap tm_a1 = make_map(enc, p_a1, DM, SEQ, 32, 8, true), tm_a2 = make_map(enc, p_a2, DM, SEQ, 32, 8, true);
  CUtensorMap tm_h2 = make_map(enc, p_h2, DM, SEQ, 64, 64);
  CUtensorMap tm_w1 = make_map(enc, w1, DFF, DM, 64, 64);
  CUtensorMap tm_w2 = make_map(enc, w2, DM, DFF, 64, 64);
  cudaFuncSetAttribute(attn_kernel, cudaFuncAttributeMaxDynamicSharedMemorySize, SM_TOTAL);
  cudaFuncSetAttribute(ffn_kernel, cudaFuncAttributeMaxDynamicSharedMemorySize, F_TOTAL);

  launch(mod_kernel, dim3(84), dim3(512), 0, false, c, wm);
  launch(ln1_kernel, dim3(SEQ / 8), dim3(256), 0, true, x);
  launch(attn_kernel, dim3(16, 8), dim3(384), SM_TOTAL, true, tm_h, tm_wq, tm_k, tm_v, tm_wo, tm_oA, tm_oAs, tm_a1);
  launch(ln2_kernel, dim3(SEQ / 8), dim3(256), 0, true, x);
  launch(ffn_kernel, dim3(32, 4), dim3(384), F_TOTAL, true, tm_h2, tm_w1, tm_w2, tm_a2, (__nv_bfloat16*)d_out);
}
```

```cpp
#include <cuda_runtime.h>
#include <cuda_bf16.h>
#include <cuda.h>
#include <stdint.h>

constexpr int SEQ = 2048, DM = 448, HKV = 8, SKV = 2048, DH = 256, WIN = 512, DFF = 1792;

__device__ __align__(1024) float          g_mod[6 * DM];
__device__ __align__(1024) __nv_bfloat16  g_h[SEQ * DM];
__device__ __align__(1024) __nv_bfloat16  g_oA[HKV * SEQ * DH];
__device__ __align__(1024) float          g_acc1[SEQ * DM];
__device__ __align__(1024) float          g_acc2[SEQ * DM];
__device__ __align__(1024) __nv_bfloat16  g_x1[SEQ * DM];
__device__ __align__(1024) __nv_bfloat16  g_h2[SEQ * DM];

__device__ __forceinline__ uint32_t smem_u32(const void* p) { return (uint32_t)__cvta_generic_to_shared(p); }
__device__ __forceinline__ void mbar_init(uint32_t bar, uint32_t cnt) {
  asm volatile("mbarrier.init.shared::cta.b64 [%0], %1;" ::"r"(bar), "r"(cnt));
}
__device__ __forceinline__ void mbar_expect_tx(uint32_t bar, uint32_t bytes) {
  asm volatile("mbarrier.arrive.expect_tx.shared::cta.b64 _, [%0], %1;" ::"r"(bar), "r"(bytes) : "memory");
}
__device__ __forceinline__ void mbar_arrive(uint32_t bar) {
  asm volatile("mbarrier.arrive.shared::cta.b64 _, [%0];" ::"r"(bar) : "memory");
}
__device__ __forceinline__ void mbar_arrive_remote(uint32_t bar, uint32_t cta) {
  asm volatile("{\n.reg .b32 ra;\nmapa.shared::cluster.u32 ra, %0, %1;\n"
               "mbarrier.arrive.shared::cluster.b64 _, [ra];\n}\n" ::"r"(bar), "r"(cta) : "memory");
}
__device__ __forceinline__ void mbar_wait(uint32_t bar, uint32_t parity) {
  asm volatile("{\n.reg .pred p;\nLAB_WAIT:\n"
               "mbarrier.try_wait.parity.shared::cta.b64 p, [%0], %1, 0x989680;\n"
               "@p bra LAB_DONE;\nbra LAB_WAIT;\nLAB_DONE:\n}\n" ::"r"(bar), "r"(parity) : "memory");
}
__device__ __forceinline__ void mbar_wait_cluster(uint32_t bar, uint32_t parity) {
  asm volatile("{\n.reg .pred p;\nLAB_WAIT:\n"
               "mbarrier.try_wait.parity.acquire.cluster.shared::cta.b64 p, [%0], %1, 0x989680;\n"
               "@p bra LAB_DONE;\nbra LAB_WAIT;\nLAB_DONE:\n}\n" ::"r"(bar), "r"(parity) : "memory");
}
__device__ __forceinline__ void tma_load(uint32_t dst, const CUtensorMap* m, int c0, int c1, uint32_t bar) {
  asm volatile("cp.async.bulk.tensor.2d.shared::cluster.global.mbarrier::complete_tx::bytes [%0], [%1, {%3, %4}], [%2];"
               ::"r"(dst), "l"(m), "r"(bar), "r"(c0), "r"(c1) : "memory");
}
__device__ __forceinline__ void tma_load_mc(uint32_t dst, const CUtensorMap* m, int c0, int c1, uint32_t bar, uint16_t mask) {
  asm volatile("cp.async.bulk.tensor.2d.shared::cluster.global.mbarrier::complete_tx::bytes.multicast::cluster [%0], [%1, {%3, %4}], [%2], %5;"
               ::"r"(dst), "l"(m), "r"(bar), "r"(c0), "r"(c1), "h"(mask) : "memory");
}
__device__ __forceinline__ void cluster_sync_all() {
  asm volatile("barrier.cluster.arrive.release.aligned;\nbarrier.cluster.wait.acquire.aligned;\n" ::: "memory");
}
__device__ __forceinline__ uint32_t cluster_rank() { uint32_t r; asm volatile("mov.u32 %0, %%cluster_ctarank;" : "=r"(r)); return r; }
__device__ __forceinline__ void wg_fence() { asm volatile("wgmma.fence.sync.aligned;" ::: "memory"); }
__device__ __forceinline__ void wg_commit() { asm volatile("wgmma.commit_group.sync.aligned;" ::: "memory"); }
template <int N> __device__ __forceinline__ void wg_wait() { asm volatile("wgmma.wait_group.sync.aligned %0;" ::"n"(N) : "memory"); }
__device__ __forceinline__ void bar_sync(int id, int n) { asm volatile("bar.sync %0, %1;" ::"r"(id), "r"(n) : "memory"); }
__device__ __forceinline__ void bar_arrive(int id, int n) { asm volatile("bar.arrive %0, %1;" ::"r"(id), "r"(n) : "memory"); }
__device__ __forceinline__ void fence_async_smem() { asm volatile("fence.proxy.async.shared::cta;" ::: "memory"); }
__device__ __forceinline__ void fence_async() { asm volatile("fence.proxy.async;" ::: "memory"); }
__device__ __forceinline__ uint64_t mk_desc(uint32_t saddr, uint32_t lbo, uint32_t sbo) {
  return (uint64_t)((saddr & 0x3FFFF) >> 4) | ((uint64_t)(lbo >> 4) << 16) | ((uint64_t)(sbo >> 4) << 32) | (1ull << 62);
}
__device__ __forceinline__ uint32_t pack_bf16(float lo, float hi) {
  uint32_t r; asm("cvt.rn.bf16x2.f32 %0, %1, %2;" : "=r"(r) : "f"(hi), "f"(lo)); return r;
}
__device__ __forceinline__ float bf_lo(uint32_t v) { return __uint_as_float(v << 16); }
__device__ __forceinline__ float bf_hi(uint32_t v) { return __uint_as_float(v & 0xFFFF0000u); }
__device__ __forceinline__ float rbf(float x) { return __bfloat162float(__float2bfloat16_rn(x)); }
__device__ __forceinline__ float ex2(float x) { float r; asm("ex2.approx.ftz.f32 %0, %1;" : "=f"(r) : "f"(x)); return r; }
__device__ __forceinline__ void red_add_v2(float* p, float a, float b) {
  asm volatile("red.global.add.v2.f32 [%0], {%1, %2};" ::"l"(p), "f"(a), "f"(b) : "memory");
}
__device__ __forceinline__ void pdl_wait() { asm volatile("griddepcontrol.wait;" ::: "memory"); }
__device__ __forceinline__ void pdl_launch() { asm volatile("griddepcontrol.launch_dependents;" ::: "memory"); }

__device__ __forceinline__ void wgmma_m64n256k16_ss_tb(float (&d)[128], uint64_t da, uint64_t db, int sc) {
  asm volatile("{\n.reg .pred p;\nsetp.ne.b32 p, %130, 0;\n"
    "wgmma.mma_async.sync.aligned.m64n256k16.f32.bf16.bf16 {%0, %1, %2, %3, %4, %5, %6, %7, %8, %9, %10, %11, %12, %13, %14, %15, %16, %17, %18, %19, %20, %21, %22, %23, %24, %25, %26, %27, %28, %29, %30, %31, %32, %33, %34, %35, %36, %37, %38, %39, %40, %41, %42, %43, %44, %45, %46, %47, %48, %49, %50, %51, %52, %53, %54, %55, %56, %57, %58, %59, %60, %61, %62, %63, %64, %65, %66, %67, %68, %69, %70, %71, %72, %73, %74, %75, %76, %77, %78, %79, %80, %81, %82, %83, %84, %85, %86, %87, %88, %89, %90, %91, %92, %93, %94, %95, %96, %97, %98, %99, %100, %101, %102, %103, %104, %105, %106, %107, %108, %109, %110, %111, %112, %113, %114, %115, %116, %117, %118, %119, %120, %121, %122, %123, %124, %125, %126, %127}, %128, %129, p, 1, 1, 0, 1;\n}\n"
    : "+f"(d[0]), "+f"(d[1]), "+f"(d[2]), "+f"(d[3]), "+f"(d[4]), "+f"(d[5]), "+f"(d[6]), "+f"(d[7]), "+f"(d[8]), "+f"(d[9]), "+f"(d[10]), "+f"(d[11]), "+f"(d[12]), "+f"(d[13]), "+f"(d[14]), "+f"(d[15]), "+f"(d[16]), "+f"(d[17]), "+f"(d[18]), "+f"(d[19]), "+f"(d[20]), "+f"(d[21]), "+f"(d[22]), "+f"(d[23]), "+f"(d[24]), "+f"(d[25]), "+f"(d[26]), "+f"(d[27]), "+f"(d[28]), "+f"(d[29]), "+f"(d[30]), "+f"(d[31]), "+f"(d[32]), "+f"(d[33]), "+f"(d[34]), "+f"(d[35]), "+f"(d[36]), "+f"(d[37]), "+f"(d[38]), "+f"(d[39]), "+f"(d[40]), "+f"(d[41]), "+f"(d[42]), "+f"(d[43]), "+f"(d[44]), "+f"(d[45]), "+f"(d[46]), "+f"(d[47]), "+f"(d[48]), "+f"(d[49]), "+f"(d[50]), "+f"(d[51]), "+f"(d[52]), "+f"(d[53]), "+f"(d[54]), "+f"(d[55]), "+f"(d[56]), "+f"(d[57]), "+f"(d[58]), "+f"(d[59]), "+f"(d[60]), "+f"(d[61]), "+f"(d[62]), "+f"(d[63]), "+f"(d[64]), "+f"(d[65]), "+f"(d[66]), "+f"(d[67]), "+f"(d[68]), "+f"(d[69]), "+f"(d[70]), "+f"(d[71]), "+f"(d[72]), "+f"(d[73]), "+f"(d[74]), "+f"(d[75]), "+f"(d[76]), "+f"(d[77]), "+f"(d[78]), "+f"(d[79]), "+f"(d[80]), "+f"(d[81]), "+f"(d[82]), "+f"(d[83]), "+f"(d[84]), "+f"(d[85]), "+f"(d[86]), "+f"(d[87]), "+f"(d[88]), "+f"(d[89]), "+f"(d[90]), "+f"(d[91]), "+f"(d[92]), "+f"(d[93]), "+f"(d[94]), "+f"(d[95]), "+f"(d[96]), "+f"(d[97]), "+f"(d[98]), "+f"(d[99]), "+f"(d[100]), "+f"(d[101]), "+f"(d[102]), "+f"(d[103]), "+f"(d[104]), "+f"(d[105]), "+f"(d[106]), "+f"(d[107]), "+f"(d[108]), "+f"(d[109]), "+f"(d[110]), "+f"(d[111]), "+f"(d[112]), "+f"(d[113]), "+f"(d[114]), "+f"(d[115]), "+f"(d[116]), "+f"(d[117]), "+f"(d[118]), "+f"(d[119]), "+f"(d[120]), "+f"(d[121]), "+f"(d[122]), "+f"(d[123]), "+f"(d[124]), "+f"(d[125]), "+f"(d[126]), "+f"(d[127])
    : "l"(da), "l"(db), "r"(sc));
}
__device__ __forceinline__ void wgmma_m64n128k16_ss(float (&d)[64], uint64_t da, uint64_t db, int sc) {
  asm volatile("{\n.reg .pred p;\nsetp.ne.b32 p, %66, 0;\n"
    "wgmma.mma_async.sync.aligned.m64n128k16.f32.bf16.bf16 {%0, %1, %2, %3, %4, %5, %6, %7, %8, %9, %10, %11, %12, %13, %14, %15, %16, %17, %18, %19, %20, %21, %22, %23, %24, %25, %26, %27, %28, %29, %30, %31, %32, %33, %34, %35, %36, %37, %38, %39, %40, %41, %42, %43, %44, %45, %46, %47, %48, %49, %50, %51, %52, %53, %54, %55, %56, %57, %58, %59, %60, %61, %62, %63}, %64, %65, p, 1, 1, 0, 0;\n}\n"
    : "+f"(d[0]), "+f"(d[1]), "+f"(d[2]), "+f"(d[3]), "+f"(d[4]), "+f"(d[5]), "+f"(d[6]), "+f"(d[7]), "+f"(d[8]), "+f"(d[9]), "+f"(d[10]), "+f"(d[11]), "+f"(d[12]), "+f"(d[13]), "+f"(d[14]), "+f"(d[15]), "+f"(d[16]), "+f"(d[17]), "+f"(d[18]), "+f"(d[19]), "+f"(d[20]), "+f"(d[21]), "+f"(d[22]), "+f"(d[23]), "+f"(d[24]), "+f"(d[25]), "+f"(d[26]), "+f"(d[27]), "+f"(d[28]), "+f"(d[29]), "+f"(d[30]), "+f"(d[31]), "+f"(d[32]), "+f"(d[33]), "+f"(d[34]), "+f"(d[35]), "+f"(d[36]), "+f"(d[37]), "+f"(d[38]), "+f"(d[39]), "+f"(d[40]), "+f"(d[41]), "+f"(d[42]), "+f"(d[43]), "+f"(d[44]), "+f"(d[45]), "+f"(d[46]), "+f"(d[47]), "+f"(d[48]), "+f"(d[49]), "+f"(d[50]), "+f"(d[51]), "+f"(d[52]), "+f"(d[53]), "+f"(d[54]), "+f"(d[55]), "+f"(d[56]), "+f"(d[57]), "+f"(d[58]), "+f"(d[59]), "+f"(d[60]), "+f"(d[61]), "+f"(d[62]), "+f"(d[63])
    : "l"(da), "l"(db), "r"(sc));
}
__device__ __forceinline__ void wgmma_m64n256k16_rs_tb(float (&d)[128], uint32_t a0, uint32_t a1, uint32_t a2, uint32_t a3, uint64_t db, int sc) {
  asm volatile("{\n.reg .pred p;\nsetp.ne.b32 p, %133, 0;\n"
    "wgmma.mma_async.sync.aligned.m64n256k16.f32.bf16.bf16 {%0, %1, %2, %3, %4, %5, %6, %7, %8, %9, %10, %11, %12, %13, %14, %15, %16, %17, %18, %19, %20, %21, %22, %23, %24, %25, %26, %27, %28, %29, %30, %31, %32, %33, %34, %35, %36, %37, %38, %39, %40, %41, %42, %43, %44, %45, %46, %47, %48, %49, %50, %51, %52, %53, %54, %55, %56, %57, %58, %59, %60, %61, %62, %63, %64, %65, %66, %67, %68, %69, %70, %71, %72, %73, %74, %75, %76, %77, %78, %79, %80, %81, %82, %83, %84, %85, %86, %87, %88, %89, %90, %91, %92, %93, %94, %95, %96, %97, %98, %99, %100, %101, %102, %103, %104, %105, %106, %107, %108, %109, %110, %111, %112, %113, %114, %115, %116, %117, %118, %119, %120, %121, %122, %123, %124, %125, %126, %127}, {%128, %129, %130, %131}, %132, p, 1, 1, 1;\n}\n"
    : "+f"(d[0]), "+f"(d[1]), "+f"(d[2]), "+f"(d[3]), "+f"(d[4]), "+f"(d[5]), "+f"(d[6]), "+f"(d[7]), "+f"(d[8]), "+f"(d[9]), "+f"(d[10]), "+f"(d[11]), "+f"(d[12]), "+f"(d[13]), "+f"(d[14]), "+f"(d[15]), "+f"(d[16]), "+f"(d[17]), "+f"(d[18]), "+f"(d[19]), "+f"(d[20]), "+f"(d[21]), "+f"(d[22]), "+f"(d[23]), "+f"(d[24]), "+f"(d[25]), "+f"(d[26]), "+f"(d[27]), "+f"(d[28]), "+f"(d[29]), "+f"(d[30]), "+f"(d[31]), "+f"(d[32]), "+f"(d[33]), "+f"(d[34]), "+f"(d[35]), "+f"(d[36]), "+f"(d[37]), "+f"(d[38]), "+f"(d[39]), "+f"(d[40]), "+f"(d[41]), "+f"(d[42]), "+f"(d[43]), "+f"(d[44]), "+f"(d[45]), "+f"(d[46]), "+f"(d[47]), "+f"(d[48]), "+f"(d[49]), "+f"(d[50]), "+f"(d[51]), "+f"(d[52]), "+f"(d[53]), "+f"(d[54]), "+f"(d[55]), "+f"(d[56]), "+f"(d[57]), "+f"(d[58]), "+f"(d[59]), "+f"(d[60]), "+f"(d[61]), "+f"(d[62]), "+f"(d[63]), "+f"(d[64]), "+f"(d[65]), "+f"(d[66]), "+f"(d[67]), "+f"(d[68]), "+f"(d[69]), "+f"(d[70]), "+f"(d[71]), "+f"(d[72]), "+f"(d[73]), "+f"(d[74]), "+f"(d[75]), "+f"(d[76]), "+f"(d[77]), "+f"(d[78]), "+f"(d[79]), "+f"(d[80]), "+f"(d[81]), "+f"(d[82]), "+f"(d[83]), "+f"(d[84]), "+f"(d[85]), "+f"(d[86]), "+f"(d[87]), "+f"(d[88]), "+f"(d[89]), "+f"(d[90]), "+f"(d[91]), "+f"(d[92]), "+f"(d[93]), "+f"(d[94]), "+f"(d[95]), "+f"(d[96]), "+f"(d[97]), "+f"(d[98]), "+f"(d[99]), "+f"(d[100]), "+f"(d[101]), "+f"(d[102]), "+f"(d[103]), "+f"(d[104]), "+f"(d[105]), "+f"(d[106]), "+f"(d[107]), "+f"(d[108]), "+f"(d[109]), "+f"(d[110]), "+f"(d[111]), "+f"(d[112]), "+f"(d[113]), "+f"(d[114]), "+f"(d[115]), "+f"(d[116]), "+f"(d[117]), "+f"(d[118]), "+f"(d[119]), "+f"(d[120]), "+f"(d[121]), "+f"(d[122]), "+f"(d[123]), "+f"(d[124]), "+f"(d[125]), "+f"(d[126]), "+f"(d[127])
    : "r"(a0), "r"(a1), "r"(a2), "r"(a3), "l"(db), "r"(sc));
}
__device__ __forceinline__ void wgmma_m64n128k16_ss_tb(float (&d)[64], uint64_t da, uint64_t db, int sc) {
  asm volatile("{\n.reg .pred p;\nsetp.ne.b32 p, %66, 0;\n"
    "wgmma.mma_async.sync.aligned.m64n128k16.f32.bf16.bf16 {%0, %1, %2, %3, %4, %5, %6, %7, %8, %9, %10, %11, %12, %13, %14, %15, %16, %17, %18, %19, %20, %21, %22, %23, %24, %25, %26, %27, %28, %29, %30, %31, %32, %33, %34, %35, %36, %37, %38, %39, %40, %41, %42, %43, %44, %45, %46, %47, %48, %49, %50, %51, %52, %53, %54, %55, %56, %57, %58, %59, %60, %61, %62, %63}, %64, %65, p, 1, 1, 0, 1;\n}\n"
    : "+f"(d[0]), "+f"(d[1]), "+f"(d[2]), "+f"(d[3]), "+f"(d[4]), "+f"(d[5]), "+f"(d[6]), "+f"(d[7]), "+f"(d[8]), "+f"(d[9]), "+f"(d[10]), "+f"(d[11]), "+f"(d[12]), "+f"(d[13]), "+f"(d[14]), "+f"(d[15]), "+f"(d[16]), "+f"(d[17]), "+f"(d[18]), "+f"(d[19]), "+f"(d[20]), "+f"(d[21]), "+f"(d[22]), "+f"(d[23]), "+f"(d[24]), "+f"(d[25]), "+f"(d[26]), "+f"(d[27]), "+f"(d[28]), "+f"(d[29]), "+f"(d[30]), "+f"(d[31]), "+f"(d[32]), "+f"(d[33]), "+f"(d[34]), "+f"(d[35]), "+f"(d[36]), "+f"(d[37]), "+f"(d[38]), "+f"(d[39]), "+f"(d[40]), "+f"(d[41]), "+f"(d[42]), "+f"(d[43]), "+f"(d[44]), "+f"(d[45]), "+f"(d[46]), "+f"(d[47]), "+f"(d[48]), "+f"(d[49]), "+f"(d[50]), "+f"(d[51]), "+f"(d[52]), "+f"(d[53]), "+f"(d[54]), "+f"(d[55]), "+f"(d[56]), "+f"(d[57]), "+f"(d[58]), "+f"(d[59]), "+f"(d[60]), "+f"(d[61]), "+f"(d[62]), "+f"(d[63])
    : "l"(da), "l"(db), "r"(sc));
}
__device__ __forceinline__ void wgmma_m64n128k16_rs_tb(float (&d)[64], uint32_t a0, uint32_t a1, uint32_t a2, uint32_t a3, uint64_t db, int sc) {
  asm volatile("{\n.reg .pred p;\nsetp.ne.b32 p, %69, 0;\n"
    "wgmma.mma_async.sync.aligned.m64n128k16.f32.bf16.bf16 {%0, %1, %2, %3, %4, %5, %6, %7, %8, %9, %10, %11, %12, %13, %14, %15, %16, %17, %18, %19, %20, %21, %22, %23, %24, %25, %26, %27, %28, %29, %30, %31, %32, %33, %34, %35, %36, %37, %38, %39, %40, %41, %42, %43, %44, %45, %46, %47, %48, %49, %50, %51, %52, %53, %54, %55, %56, %57, %58, %59, %60, %61, %62, %63}, {%64, %65, %66, %67}, %68, p, 1, 1, 1;\n}\n"
    : "+f"(d[0]), "+f"(d[1]), "+f"(d[2]), "+f"(d[3]), "+f"(d[4]), "+f"(d[5]), "+f"(d[6]), "+f"(d[7]), "+f"(d[8]), "+f"(d[9]), "+f"(d[10]), "+f"(d[11]), "+f"(d[12]), "+f"(d[13]), "+f"(d[14]), "+f"(d[15]), "+f"(d[16]), "+f"(d[17]), "+f"(d[18]), "+f"(d[19]), "+f"(d[20]), "+f"(d[21]), "+f"(d[22]), "+f"(d[23]), "+f"(d[24]), "+f"(d[25]), "+f"(d[26]), "+f"(d[27]), "+f"(d[28]), "+f"(d[29]), "+f"(d[30]), "+f"(d[31]), "+f"(d[32]), "+f"(d[33]), "+f"(d[34]), "+f"(d[35]), "+f"(d[36]), "+f"(d[37]), "+f"(d[38]), "+f"(d[39]), "+f"(d[40]), "+f"(d[41]), "+f"(d[42]), "+f"(d[43]), "+f"(d[44]), "+f"(d[45]), "+f"(d[46]), "+f"(d[47]), "+f"(d[48]), "+f"(d[49]), "+f"(d[50]), "+f"(d[51]), "+f"(d[52]), "+f"(d[53]), "+f"(d[54]), "+f"(d[55]), "+f"(d[56]), "+f"(d[57]), "+f"(d[58]), "+f"(d[59]), "+f"(d[60]), "+f"(d[61]), "+f"(d[62]), "+f"(d[63])
    : "r"(a0), "r"(a1), "r"(a2), "r"(a3), "l"(db), "r"(sc));
}
__device__ __forceinline__ void wgmma_m64n64k16_ss_tb(float (&d)[32], uint64_t da, uint64_t db, int sc) {
  asm volatile("{\n.reg .pred p;\nsetp.ne.b32 p, %34, 0;\n"
    "wgmma.mma_async.sync.aligned.m64n64k16.f32.bf16.bf16 {%0, %1, %2, %3, %4, %5, %6, %7, %8, %9, %10, %11, %12, %13, %14, %15, %16, %17, %18, %19, %20, %21, %22, %23, %24, %25, %26, %27, %28, %29, %30, %31}, %32, %33, p, 1, 1, 0, 1;\n}\n"
    : "+f"(d[0]), "+f"(d[1]), "+f"(d[2]), "+f"(d[3]), "+f"(d[4]), "+f"(d[5]), "+f"(d[6]), "+f"(d[7]), "+f"(d[8]), "+f"(d[9]), "+f"(d[10]), "+f"(d[11]), "+f"(d[12]), "+f"(d[13]), "+f"(d[14]), "+f"(d[15]), "+f"(d[16]), "+f"(d[17]), "+f"(d[18]), "+f"(d[19]), "+f"(d[20]), "+f"(d[21]), "+f"(d[22]), "+f"(d[23]), "+f"(d[24]), "+f"(d[25]), "+f"(d[26]), "+f"(d[27]), "+f"(d[28]), "+f"(d[29]), "+f"(d[30]), "+f"(d[31])
    : "l"(da), "l"(db), "r"(sc));
}
__device__ __forceinline__ void wgmma_m64n64k16_rs_tb(float (&d)[32], uint32_t a0, uint32_t a1, uint32_t a2, uint32_t a3, uint64_t db, int sc) {
  asm volatile("{\n.reg .pred p;\nsetp.ne.b32 p, %37, 0;\n"
    "wgmma.mma_async.sync.aligned.m64n64k16.f32.bf16.bf16 {%0, %1, %2, %3, %4, %5, %6, %7, %8, %9, %10, %11, %12, %13, %14, %15, %16, %17, %18, %19, %20, %21, %22, %23, %24, %25, %26, %27, %28, %29, %30, %31}, {%32, %33, %34, %35}, %36, p, 1, 1, 1;\n}\n"
    : "+f"(d[0]), "+f"(d[1]), "+f"(d[2]), "+f"(d[3]), "+f"(d[4]), "+f"(d[5]), "+f"(d[6]), "+f"(d[7]), "+f"(d[8]), "+f"(d[9]), "+f"(d[10]), "+f"(d[11]), "+f"(d[12]), "+f"(d[13]), "+f"(d[14]), "+f"(d[15]), "+f"(d[16]), "+f"(d[17]), "+f"(d[18]), "+f"(d[19]), "+f"(d[20]), "+f"(d[21]), "+f"(d[22]), "+f"(d[23]), "+f"(d[24]), "+f"(d[25]), "+f"(d[26]), "+f"(d[27]), "+f"(d[28]), "+f"(d[29]), "+f"(d[30]), "+f"(d[31])
    : "r"(a0), "r"(a1), "r"(a2), "r"(a3), "l"(db), "r"(sc));
}
__device__ __forceinline__ void wgmma_m64n192k16_ss_tb(float (&d)[128], uint64_t da, uint64_t db, int sc) {
  asm volatile("{\n.reg .pred p;\nsetp.ne.b32 p, %98, 0;\n"
    "wgmma.mma_async.sync.aligned.m64n192k16.f32.bf16.bf16 {%0, %1, %2, %3, %4, %5, %6, %7, %8, %9, %10, %11, %12, %13, %14, %15, %16, %17, %18, %19, %20, %21, %22, %23, %24, %25, %26, %27, %28, %29, %30, %31, %32, %33, %34, %35, %36, %37, %38, %39, %40, %41, %42, %43, %44, %45, %46, %47, %48, %49, %50, %51, %52, %53, %54, %55, %56, %57, %58, %59, %60, %61, %62, %63, %64, %65, %66, %67, %68, %69, %70, %71, %72, %73, %74, %75, %76, %77, %78, %79, %80, %81, %82, %83, %84, %85, %86, %87, %88, %89, %90, %91, %92, %93, %94, %95}, %96, %97, p, 1, 1, 0, 1;\n}\n"
    : "+f"(d[0]), "+f"(d[1]), "+f"(d[2]), "+f"(d[3]), "+f"(d[4]), "+f"(d[5]), "+f"(d[6]), "+f"(d[7]), "+f"(d[8]), "+f"(d[9]), "+f"(d[10]), "+f"(d[11]), "+f"(d[12]), "+f"(d[13]), "+f"(d[14]), "+f"(d[15]), "+f"(d[16]), "+f"(d[17]), "+f"(d[18]), "+f"(d[19]), "+f"(d[20]), "+f"(d[21]), "+f"(d[22]), "+f"(d[23]), "+f"(d[24]), "+f"(d[25]), "+f"(d[26]), "+f"(d[27]), "+f"(d[28]), "+f"(d[29]), "+f"(d[30]), "+f"(d[31]), "+f"(d[32]), "+f"(d[33]), "+f"(d[34]), "+f"(d[35]), "+f"(d[36]), "+f"(d[37]), "+f"(d[38]), "+f"(d[39]), "+f"(d[40]), "+f"(d[41]), "+f"(d[42]), "+f"(d[43]), "+f"(d[44]), "+f"(d[45]), "+f"(d[46]), "+f"(d[47]), "+f"(d[48]), "+f"(d[49]), "+f"(d[50]), "+f"(d[51]), "+f"(d[52]), "+f"(d[53]), "+f"(d[54]), "+f"(d[55]), "+f"(d[56]), "+f"(d[57]), "+f"(d[58]), "+f"(d[59]), "+f"(d[60]), "+f"(d[61]), "+f"(d[62]), "+f"(d[63]), "+f"(d[64]), "+f"(d[65]), "+f"(d[66]), "+f"(d[67]), "+f"(d[68]), "+f"(d[69]), "+f"(d[70]), "+f"(d[71]), "+f"(d[72]), "+f"(d[73]), "+f"(d[74]), "+f"(d[75]), "+f"(d[76]), "+f"(d[77]), "+f"(d[78]), "+f"(d[79]), "+f"(d[80]), "+f"(d[81]), "+f"(d[82]), "+f"(d[83]), "+f"(d[84]), "+f"(d[85]), "+f"(d[86]), "+f"(d[87]), "+f"(d[88]), "+f"(d[89]), "+f"(d[90]), "+f"(d[91]), "+f"(d[92]), "+f"(d[93]), "+f"(d[94]), "+f"(d[95])
    : "l"(da), "l"(db), "r"(sc));
}

#define TM(id)
#define GT_MIN(i)
#define GT_MAX(i)

constexpr int NS = 5;
constexpr uint32_t STG = 32768;
constexpr uint32_t SM_Q = 0;
constexpr uint32_t SM_RING = 65536;
constexpr uint32_t SM_BAR = SM_RING + NS * STG;
constexpr uint32_t SM_TOTAL = SM_BAR + 256 + 1024;

struct Ring {
  uint32_t base, full0, empty0, st, ph, nst, stg;
  __device__ __forceinline__ void init(uint32_t sb) { base = sb + SM_RING; full0 = sb + SM_BAR; empty0 = sb + SM_BAR + 64; st = 0; ph = 0; nst = NS; stg = STG; }
  __device__ __forceinline__ uint32_t phase() const { return (ph >> st) & 1; }
  __device__ __forceinline__ uint32_t buf() const { return base + st * stg; }
  __device__ __forceinline__ uint32_t full() const { return full0 + st * 8; }
  __device__ __forceinline__ uint32_t empty() const { return empty0 + st * 8; }
  __device__ __forceinline__ void next() { ph ^= 1u << st; st = (st + 1 >= nst) ? 0 : st + 1; }
  __device__ __forceinline__ void shrink() { nst = NS - 1; if (st >= nst) st = 0; }
  __device__ __forceinline__ uint32_t acquire(uint32_t bytes) {
    mbar_wait(empty(), phase() ^ 1); mbar_expect_tx(full(), bytes); return buf();
  }
  __device__ __forceinline__ uint32_t wait() { mbar_wait(full(), phase()); return buf(); }
};
template <int CL = 2>
__device__ __forceinline__ void ring_release(uint32_t empty_bar, int lane) {
  __syncwarp();
  if (lane < CL) mbar_arrive_remote(empty_bar, (uint32_t)lane);
}

template <int CL>
__device__ __forceinline__ void gemm_k448_n256(Ring& r, float (&acc)[128], int wg, int lane) {
  uint32_t hb = 0, hrel = 0, prel = 0, phrel = 0;
#pragma unroll
  for (int c = 0; c < 7; ++c) {
    if ((c & 1) == 0) { hb = r.wait(); hrel = r.empty(); r.next(); }
    uint32_t wb = r.wait(); uint32_t wrel = r.empty(); r.next();
    uint64_t da = mk_desc(hb + (c & 1) * 16384 + wg * 8192, 16, 1024);
    uint64_t db = mk_desc(wb, 8192, 1024);
    wg_fence();
#pragma unroll
    for (int k = 0; k < 4; ++k) wgmma_m64n256k16_ss_tb(acc, da + k * 2, db + k * 128, (c | k) != 0);
    wg_commit();
    if (c > 0) {
      wg_wait<1>();
      ring_release<CL>(prel, lane);
      if ((c & 1) == 0) ring_release<CL>(phrel, lane);
    }
    prel = wrel; phrel = hrel;
  }
  wg_wait<0>();
  ring_release<CL>(prel, lane); ring_release<CL>(phrel, lane);
}

template <bool RELU>
__device__ __forceinline__ void store_tile_bf16(uint32_t base, const float (&acc)[128], int rloc, int t4) {
  uint32_t row0 = base + rloc * 128, row1 = row0 + 8 * 128;
  uint32_t sw = (uint32_t)(rloc & 7);
#pragma unroll
  for (int j = 0; j < 32; ++j) {
    uint32_t off = (uint32_t)(j >> 3) * 16384 + ((((uint32_t)j & 7) ^ sw) << 4) + t4 * 4;
    float a = acc[4 * j], b = acc[4 * j + 1], c = acc[4 * j + 2], d = acc[4 * j + 3];
    if (RELU) { a = fmaxf(a, 0.f); b = fmaxf(b, 0.f); c = fmaxf(c, 0.f); d = fmaxf(d, 0.f); }
    asm volatile("st.shared.b32 [%0], %1;" ::"r"(row0 + off), "r"(pack_bf16(a, b)) : "memory");
    asm volatile("st.shared.b32 [%0], %1;" ::"r"(row1 + off), "r"(pack_bf16(c, d)) : "memory");
  }
}

template <int NJ, int OFF = 0, int SZ = 64, bool WAIT = true>
__device__ __forceinline__ void red_rows(uint32_t stg, const CUtensorMap* tm, int row0, int col0, const float (&a)[SZ], int sel, int lane) {
  asm volatile("" : "+r"(stg), "+r"(lane));
  if (WAIT) {
    if (lane == 0) asm volatile("cp.async.bulk.wait_group.read 0;" ::: "memory");
    __syncwarp();
  }
  const uint32_t g = lane >> 2, t4 = lane & 3;
  const uint32_t wbase = stg + g * 128 + (t4 & 1) * 8;
#pragma unroll
  for (int j = 0; j < NJ; ++j)
    asm volatile("st.shared.v2.f32 [%0], {%1, %2};" ::"r"(wbase + (j >> 2) * 1024 + ((((j & 3) * 2 + (t4 >> 1)) ^ g) << 4)),
                 "f"(a[OFF + 4 * j + sel]), "f"(a[OFF + 4 * j + sel + 1]) : "memory");
  fence_async_smem();
  __syncwarp();
  if (lane == 0) {
#pragma unroll
    for (int b = 0; b < NJ / 4; ++b)
      asm volatile("cp.reduce.async.bulk.tensor.2d.global.shared::cta.add.tile.bulk_group [%0, {%2, %3}], [%1];"
                   ::"l"(tm), "r"(stg + b * 1024), "r"(col0 + b * 32), "r"(row0) : "memory");
    asm volatile("cp.async.bulk.commit_group;" ::: "memory");
  }
}

template <int NSM, int NRG, int CL>
__device__ __forceinline__ void out_proj(Ring& r, const uint32_t (&ob)[64], uint32_t abase,
                                         const CUtensorMap* tm, int roww, uint32_t stg, int lane) {
  constexpr int NST = (NSM + NRG) / 2;
  uint32_t prel = 0;
  float accA[64], accB[64];
  float(&cur32)[32] = *reinterpret_cast<float(*)[32]>(&accB[0]);
#pragma unroll
  for (int pass = 0; pass < 4; ++pass) {
    float(&cur)[64] = (pass & 1) ? accB : accA;
    float(&prv)[64] = (pass & 1) ? accA : accB;
#pragma unroll
    for (int st = 0; st < NST; ++st) {
      uint32_t wb = r.wait(); uint32_t rel = r.empty(); r.next();
      asm volatile("" : "+r"(abase));
      wg_fence();
#pragma unroll
      for (int cc = 0; cc < 2; ++cc) {
        const int c = 2 * st + cc;
#pragma unroll
        for (int k = 0; k < 4; ++k) {
          const int sc = (c | k) != 0;
          if (pass < 3) {
            uint64_t db = mk_desc(wb + cc * 16384 + k * 2048, 8192, 1024);
            if (c < NSM) wgmma_m64n128k16_ss_tb(cur, mk_desc(abase + c * 16384 + k * 32, 16, 1024), db, sc);
            else { const int o = (c - NSM) * 16 + 4 * k; wgmma_m64n128k16_rs_tb(cur, ob[o], ob[o + 1], ob[o + 2], ob[o + 3], db, sc); }
          } else {
            uint64_t db = mk_desc(wb + cc * 8192 + k * 2048, 8192, 1024);
            if (c < NSM) wgmma_m64n64k16_ss_tb(cur32, mk_desc(abase + c * 16384 + k * 32, 16, 1024), db, sc);
            else { const int o = (c - NSM) * 16 + 4 * k; wgmma_m64n64k16_rs_tb(cur32, ob[o], ob[o + 1], ob[o + 2], ob[o + 3], db, sc); }
          }
        }
      }
      wg_commit();
      if (pass | st) { wg_wait<1>(); ring_release<CL>(prel, lane); }
      prel = rel;
      if (pass > 0) {
        if (st == 0) red_rows<16>(stg, tm, roww, (pass - 1) * 128, prv, 0, lane);
        if (st == NST / 2) red_rows<16>(stg, tm, roww + 8, (pass - 1) * 128, prv, 2, lane);
      }
    }
  }
  wg_wait<0>(); ring_release<CL>(prel, lane);
  red_rows<8>(stg, tm, roww, 384, accB, 0, lane);
  red_rows<8>(stg, tm, roww + 8, 384, accB, 2, lane);
  if (lane == 0) asm volatile("cp.async.bulk.wait_group 0;" ::: "memory");
}
template <int CL>
__device__ __forceinline__ void out_proj_loads(Ring& r, const CUtensorMap* tm, int krow0, int nch, uint32_t rank) {
  r.shrink();
  constexpr uint16_t MASK = (1 << CL) - 1;
  for (int pass = 0; pass < 4; ++pass)
    for (int st = 0; st < nch / 2; ++st) {
      if (pass < 3) {
        uint32_t b = r.acquire(32768);
        for (int x = 0; x < 4 / CL; ++x) {
          const int bx = rank * (4 / CL) + x;
          tma_load_mc(b + bx * 8192, tm, pass * 128 + (bx & 1) * 64, krow0 + (2 * st + (bx >> 1)) * 64, r.full(), MASK);
        }
      } else {
        uint32_t b = r.acquire(16384);
        if (CL == 1) { for (int x = 0; x < 2; ++x) tma_load_mc(b + x * 8192, tm, 384, krow0 + (2 * st + x) * 64, r.full(), MASK); }
        else if (rank < 2) tma_load_mc(b + rank * 8192, tm, 384, krow0 + (2 * st + rank) * 64, r.full(), MASK);
      }
      r.next();
    }
}

#define ACL 2
__global__ void __cluster_dims__(ACL, 1, 1) __launch_bounds__(384, 1)
attn_kernel(const __grid_constant__ CUtensorMap tm_h, const __grid_constant__ CUtensorMap tm_wq,
            const __grid_constant__ CUtensorMap tm_k, const __grid_constant__ CUtensorMap tm_v,
            const __grid_constant__ CUtensorMap tm_wo, const __grid_constant__ CUtensorMap tm_oA,
            const __grid_constant__ CUtensorMap tm_oAs, const __grid_constant__ CUtensorMap tm_acc) {
  extern __shared__ uint8_t smem_raw[];
  const uint32_t sb = (smem_u32(smem_raw) + 1023) & ~1023u;
  const int tid = threadIdx.x, wg = tid >> 7, lane = tid & 31;
  const int qt = blockIdx.x, kvh = blockIdx.y;
  const uint32_t rank = cluster_rank();
  Ring r; r.init(sb);
  const uint32_t bar_oA = sb + SM_BAR + 128, bar_oAf = sb + SM_BAR + 136;
  if (tid == 0) {
    for (int i = 0; i < NS; ++i) { mbar_init(r.full0 + 8 * i, 1); mbar_init(r.empty0 + 8 * i, 8 * ACL); }
    mbar_init(bar_oA, 256); mbar_init(bar_oAf, 1);
    asm volatile("fence.mbarrier_init.release.cluster;" ::: "memory");
  }
  cluster_sync_all();
  pdl_wait();
  GT_MIN(4);

  if (wg == 2) {
    asm volatile("setmaxnreg.dec.sync.aligned.u32 24;");
    if (tid == 256) {
      const int krow0 = kvh * SKV + (SKV - WIN);
      for (int hh = 0; hh < 2; ++hh) {
        const int head = kvh * 2 + hh;
        for (int p = 0; p < 4; ++p) {
          int nc = (p < 3) ? 2 : 1;
          uint32_t b = r.acquire(nc * 16384);
          for (int c = 0; c < nc; ++c) tma_load(b + c * 16384, &tm_h, (2 * p + c) * 64, qt * 128, r.full());
          r.next();
          for (int c = 0; c < nc; ++c) {
            b = r.acquire(32768);
            for (int x = 0; x < 4 / ACL; ++x) {
              int bx = rank * 2 + x;
              tma_load_mc(b + bx * 8192, &tm_wq, head * 256 + bx * 64, (2 * p + c) * 64, r.full(), (1 << ACL) - 1);
            }
            r.next();
          }
        }
        for (int t = 0; t < 4; ++t) {
          for (int hf = 0; hf < 2; ++hf) {
            uint32_t b = r.acquire(32768);
            for (int x = 0; x < 2 / ACL; ++x)
              tma_load_mc(b + (rank + x) * 16384, &tm_k, (2 * hf + rank + x) * 64, krow0 + t * 128, r.full(), (1 << ACL) - 1);
            r.next();
          }
          for (int hf = 0; hf < 2; ++hf) {
            uint32_t b = r.acquire(32768);
            for (int x = 0; x < 4 / ACL; ++x) {
              int bx = rank * 2 + x;
              tma_load_mc(b + bx * 8192, &tm_v, bx * 64, krow0 + t * 128 + hf * 64, r.full(), (1 << ACL) - 1);
            }
            r.next();
          }
        }
      }
      mbar_wait(bar_oA, 0);
      mbar_expect_tx(bar_oAf, 65536);
      for (int c = 0; c < 4; ++c) tma_load(sb + SM_Q + c * 16384, &tm_oA, c * 64, kvh * SEQ + qt * 128, bar_oAf);
      out_proj_loads<ACL>(r, &tm_wo, kvh * 512, 8, rank);
    }
  } else {
    asm volatile("setmaxnreg.inc.sync.aligned.u32 240;");
    const int warp = (tid >> 5) & 3, g = lane >> 2, t4 = lane & 3;
    const int rloc = wg * 64 + warp * 16 + g;
    uint32_t ob[64];
    float acc[128];
    const float CS = 1.4426950408889634f * 0.0625f;
    TM(0);
#pragma unroll 1
    for (int hh = 0; hh < 2; ++hh) {
      gemm_k448_n256<ACL>(r, acc, wg, lane);
      TM(1);
      if (hh == 1) {
        if ((tid & 127) == 0) asm volatile("cp.async.bulk.wait_group.read 0;" ::: "memory");
        bar_sync(1 + wg, 128);
      }
      store_tile_bf16<false>(sb + SM_Q, acc, rloc, t4);
      fence_async_smem();
      bar_sync(1 + wg, 128);
      float m0 = -INFINITY, m1 = -INFINITY, l0 = 0.f, l1 = 0.f;
      const uint32_t qa0 = sb + SM_Q + wg * 8192;
      if (wg == 1) bar_arrive(3, 256);
      TM(2);
      bar_sync(3 + wg, 256);
#pragma unroll 1
      for (int t = 0; t < 4; ++t) {
        float s[64];
        TM(3);
        {
          uint32_t qa = qa0; asm volatile("" : "+r"(qa));
          uint32_t ka = r.wait(); uint32_t rel0 = r.empty(); r.next();
          wg_fence();
#pragma unroll
          for (int k = 0; k < 8; ++k)
            wgmma_m64n128k16_ss(s, mk_desc(qa + (k >> 2) * 16384 + (k & 3) * 32, 16, 1024),
                                mk_desc(ka + (k >> 2) * 16384 + (k & 3) * 32, 16, 1024), k != 0);
          wg_commit();
          uint32_t kb = r.wait(); uint32_t rel1 = r.empty(); r.next();
          wg_fence();
#pragma unroll
          for (int k = 0; k < 8; ++k)
            wgmma_m64n128k16_ss(s, mk_desc(qa + (2 + (k >> 2)) * 16384 + (k & 3) * 32, 16, 1024),
                                mk_desc(kb + (k >> 2) * 16384 + (k & 3) * 32, 16, 1024), 1);
          wg_commit();
          bar_arrive(4 - wg, 256);
          wg_wait<1>(); ring_release<ACL>(rel0, lane);
          wg_wait<0>(); ring_release<ACL>(rel1, lane);
        }
        TM(4);
        float mx0 = m0, mx1 = m1;
#pragma unroll
        for (int j = 0; j < 16; ++j) {
          uint32_t a = pack_bf16(s[4 * j], s[4 * j + 1]), b = pack_bf16(s[4 * j + 2], s[4 * j + 3]);
          s[4 * j] = bf_lo(a); s[4 * j + 1] = bf_hi(a); s[4 * j + 2] = bf_lo(b); s[4 * j + 3] = bf_hi(b);
          mx0 = fmaxf(mx0, fmaxf(s[4 * j], s[4 * j + 1])); mx1 = fmaxf(mx1, fmaxf(s[4 * j + 2], s[4 * j + 3]));
        }
        mx0 = fmaxf(mx0, __shfl_xor_sync(0xffffffffu, mx0, 1)); mx0 = fmaxf(mx0, __shfl_xor_sync(0xffffffffu, mx0, 2));
        mx1 = fmaxf(mx1, __shfl_xor_sync(0xffffffffu, mx1, 1)); mx1 = fmaxf(mx1, __shfl_xor_sync(0xffffffffu, mx1, 2));
        const float c0 = ex2((m0 - mx0) * CS), c1 = ex2((m1 - mx1) * CS);
        m0 = mx0; m1 = mx1;
        const float nb0 = -mx0 * CS, nb1 = -mx1 * CS;
        float ps0 = 0.f, ps1 = 0.f;
        uint32_t pa[32];
#pragma unroll
        for (int j = 0; j < 16; ++j) {
          float e0 = ex2(fmaf(s[4 * j], CS, nb0)), e1 = ex2(fmaf(s[4 * j + 1], CS, nb0));
          float e2 = ex2(fmaf(s[4 * j + 2], CS, nb1)), e3 = ex2(fmaf(s[4 * j + 3], CS, nb1));
          ps0 += e0 + e1; ps1 += e2 + e3;
          pa[2 * j] = pack_bf16(e0, e1); pa[2 * j + 1] = pack_bf16(e2, e3);
        }
        l0 = l0 * c0 + ps0; l1 = l1 * c1 + ps1;
        if (t > 0) {
#pragma unroll
          for (int j = 0; j < 32; ++j) { acc[4 * j] *= c0; acc[4 * j + 1] *= c0; acc[4 * j + 2] *= c1; acc[4 * j + 3] *= c1; }
        }
#pragma unroll
        for (int j = 0; j < 32; ++j) asm volatile("" : "+r"(pa[j]));
#pragma unroll
        for (int j = 0; j < 128; ++j) asm volatile("" : "+f"(acc[j]));
        asm volatile("" : "+f"(l0), "+f"(l1));
        TM(5);
        bar_sync(3 + wg, 256);
        TM(6);
        {
          uint32_t va = r.wait(); uint32_t rel0 = r.empty(); r.next();
          wg_fence();
#pragma unroll
          for (int k = 0; k < 4; ++k)
            wgmma_m64n256k16_rs_tb(acc, pa[4 * k], pa[4 * k + 1], pa[4 * k + 2], pa[4 * k + 3],
                                   mk_desc(va + k * 2048, 8192, 1024), (t | k) != 0);
          wg_commit();
          uint32_t vb = r.wait(); uint32_t rel1 = r.empty(); r.next();
          wg_fence();
#pragma unroll
          for (int k = 0; k < 4; ++k)
            wgmma_m64n256k16_rs_tb(acc, pa[16 + 4 * k], pa[16 + 4 * k + 1], pa[16 + 4 * k + 2], pa[16 + 4 * k + 3],
                                   mk_desc(vb + k * 2048, 8192, 1024), 1);
          wg_commit();
          if (t == 3 && wg == 0) bar_arrive(4, 256);
          wg_wait<1>(); ring_release<ACL>(rel0, lane);
          wg_wait<0>(); ring_release<ACL>(rel1, lane);
        }
      }
      TM(7);
      l0 += __shfl_xor_sync(0xffffffffu, l0, 1); l0 += __shfl_xor_sync(0xffffffffu, l0, 2);
      l1 += __shfl_xor_sync(0xffffffffu, l1, 1); l1 += __shfl_xor_sync(0xffffffffu, l1, 2);
      const float i0 = 1.f / l0, i1 = 1.f / l1;
#pragma unroll
      for (int j = 0; j < 32; ++j) {
        ob[2 * j] = pack_bf16(acc[4 * j] * i0, acc[4 * j + 1] * i0);
        ob[2 * j + 1] = pack_bf16(acc[4 * j + 2] * i1, acc[4 * j + 3] * i1);
      }
      if (hh == 0) {
        uint32_t row0 = sb + SM_Q + rloc * 128, row1 = row0 + 8 * 128;
        uint32_t sw = (uint32_t)(rloc & 7);
#pragma unroll
        for (int j = 0; j < 32; ++j) {
          uint32_t off = (uint32_t)(j >> 3) * 16384 + ((((uint32_t)j & 7) ^ sw) << 4) + t4 * 4;
          asm volatile("st.shared.b32 [%0], %1;" ::"r"(row0 + off), "r"(ob[2 * j]) : "memory");
          asm volatile("st.shared.b32 [%0], %1;" ::"r"(row1 + off), "r"(ob[2 * j + 1]) : "memory");
        }
        fence_async_smem();
        bar_sync(1 + wg, 128);
        if ((tid & 127) == 0) {
          for (int c = 0; c < 4; ++c)
            asm volatile("cp.async.bulk.tensor.2d.global.shared::cta.bulk_group [%0, {%2, %3}], [%1];"
                         ::"l"(&tm_oAs), "r"(sb + SM_Q + c * 16384 + wg * 8192), "r"(c * 64), "r"(kvh * SEQ + qt * 128 + wg * 64) : "memory");
          asm volatile("cp.async.bulk.commit_group;" ::: "memory");
        }
      }
    }
    if ((tid & 127) == 0) asm volatile("cp.async.bulk.wait_group 0;" ::: "memory");
    mbar_arrive(bar_oA);
    mbar_wait(bar_oAf, 0);
    TM(8);
    r.shrink();
    out_proj<4, 4, ACL>(r, ob, sb + SM_Q + wg * 8192, &tm_acc, qt * 128 + wg * 64 + warp * 16,
                   sb + SM_RING + (NS - 1) * STG + (wg * 4 + warp) * 4096, lane);
    TM(9);
  }
  cluster_sync_all();
  GT_MAX(5);
}

constexpr uint32_t F_STG = 57344, F_A = 0, F_RING = 57344, F_BAR = F_RING + 3 * F_STG, F_TOTAL = F_BAR + 256 + 1024;

template <int WG>
__device__ __forceinline__ void ffn_gemm(Ring& r, float (&acc)[128], uint32_t abase, int lane) {
  uint32_t prel = 0;
#pragma unroll
  for (int c = 0; c < 7; ++c) {
    uint32_t wb = r.wait(); uint32_t wrel = r.empty(); r.next();
    uint64_t da = mk_desc(abase + c * 8192, 16, 1024);
    uint64_t db = mk_desc(wb + WG * 32768, 8192, 1024);
    wg_fence();
#pragma unroll
    for (int k = 0; k < 4; ++k) {
      if (WG == 0) wgmma_m64n256k16_ss_tb(acc, da + k * 2, db + k * 128, (c | k) != 0);
      else wgmma_m64n192k16_ss_tb(acc, da + k * 2, db + k * 128, (c | k) != 0);
    }
    wg_commit();
    if (c > 0) { wg_wait<1>(); ring_release<2>(prel, lane); }
    prel = wrel;
  }
  wg_wait<0>();
  ring_release<2>(prel, lane);
}

template <int WG>
__device__ __forceinline__ void ffn_consumer(Ring& r, uint32_t sb, uint32_t bar_a, int rt, int warp, int lane, const CUtensorMap* tm) {
  const int g = lane >> 2, t4 = lane & 3, row = warp * 16 + g;
  float acc[128];
  TM(20);
  mbar_wait(bar_a, 0);
  TM(21);
  ffn_gemm<WG>(r, acc, sb + F_A, lane);
  TM(22);
  bar_sync(5, 256);
  {
    uint32_t row0 = sb + F_A + WG * 32768 + row * 128, row1 = row0 + 8 * 128;
    uint32_t sw = (uint32_t)(row & 7);
#pragma unroll
    for (int j = 0; j < (WG == 0 ? 32 : 24); ++j) {
      uint32_t off = (uint32_t)(j >> 3) * 8192 + ((((uint32_t)j & 7) ^ sw) << 4) + t4 * 4;
      asm volatile("st.shared.b32 [%0], %1;" ::"r"(row0 + off), "r"(pack_bf16(fmaxf(acc[4 * j], 0.f), fmaxf(acc[4 * j + 1], 0.f))) : "memory");
      asm volatile("st.shared.b32 [%0], %1;" ::"r"(row1 + off), "r"(pack_bf16(fmaxf(acc[4 * j + 2], 0.f), fmaxf(acc[4 * j + 3], 0.f))) : "memory");
    }
  }
  fence_async_smem();
  bar_sync(5, 256);
  TM(23);
  ffn_gemm<WG>(r, acc, sb + F_A, lane);
  TM(24);
  bar_sync(5, 256);
  const int r0 = rt * 64 + warp * 16, c0 = WG * 256;
  const uint32_t stg = sb + (WG * 4 + warp) * 16384;
  red_rows<16, 0, 128, false>(stg, tm, r0, c0, acc, 0, lane);
  red_rows<16, 0, 128, false>(stg + 4096, tm, r0 + 8, c0, acc, 2, lane);
  if (WG == 0) {
    red_rows<16, 64, 128, false>(stg + 8192, tm, r0, c0 + 128, acc, 0, lane);
    red_rows<16, 64, 128, false>(stg + 12288, tm, r0 + 8, c0 + 128, acc, 2, lane);
  } else {
    red_rows<8, 64, 128, false>(stg + 8192, tm, r0, c0 + 128, acc, 0, lane);
    red_rows<8, 64, 128, false>(stg + 12288, tm, r0 + 8, c0 + 128, acc, 2, lane);
  }
  if (lane == 0) asm volatile("cp.async.bulk.wait_group 0;" ::: "memory");
  TM(25);
}

__global__ void __cluster_dims__(2, 1, 1) __launch_bounds__(384, 1)
ffn_kernel(const __grid_constant__ CUtensorMap tm_h2, const __grid_constant__ CUtensorMap tm_w1,
           const __grid_constant__ CUtensorMap tm_w2, const __grid_constant__ CUtensorMap tm_acc) {
  extern __shared__ uint8_t smem_raw[];
  const uint32_t sb = (smem_u32(smem_raw) + 1023) & ~1023u;
  const int tid = threadIdx.x, wg = tid >> 7, lane = tid & 31;
  const int rt = blockIdx.x, sl = blockIdx.y;
  const uint32_t rank = cluster_rank();
  Ring r; r.base = sb + F_RING; r.full0 = sb + F_BAR; r.empty0 = sb + F_BAR + 64; r.st = 0; r.ph = 0; r.nst = 3; r.stg = F_STG;
  const uint32_t bar_a = sb + F_BAR + 128;
  if (tid == 0) {
    for (int i = 0; i < 3; ++i) { mbar_init(r.full0 + 8 * i, 1); mbar_init(r.empty0 + 8 * i, 16); }
    mbar_init(bar_a, 1);
    asm volatile("fence.mbarrier_init.release.cluster;" ::: "memory");
  }
  cluster_sync_all();
  if (wg == 2) {
    asm volatile("setmaxnreg.dec.sync.aligned.u32 24;");
    if (tid == 256) {
      const int b0 = rank ? 4 : 0, b1 = rank ? 7 : 4;
      pdl_wait();
      mbar_expect_tx(bar_a, 57344);
      for (int k = 0; k < 7; ++k) tma_load(sb + F_A + k * 8192, &tm_h2, k * 64, rt * 64, bar_a);
      for (int c = 0; c < 14; ++c) {
        uint32_t b = r.acquire(F_STG);
        for (int bx = b0; bx < b1; ++bx) {
          if (c < 7) tma_load_mc(b + bx * 8192, &tm_w1, sl * 448 + bx * 64, c * 64, r.full(), 3);
          else tma_load_mc(b + bx * 8192, &tm_w2, bx * 64, sl * 448 + (c - 7) * 64, r.full(), 3);
        }
        r.next();
      }
    }
  } else {
    asm volatile("setmaxnreg.inc.sync.aligned.u32 240;");
    pdl_wait();
    GT_MIN(8);
    const int warp = (tid >> 5) & 3;
    if (wg == 0) ffn_consumer<0>(r, sb, bar_a, rt, warp, lane, &tm_acc);
    else ffn_consumer<1>(r, sb, bar_a, rt, warp, lane, &tm_acc);
  }
  cluster_sync_all();
  GT_MAX(9);
}

__global__ void __launch_bounds__(512) mod_kernel(const __nv_bfloat16* __restrict__ c, const __nv_bfloat16* __restrict__ wm) {
  __shared__ float red[32][33];
  const int tid = threadIdx.x;
  pdl_launch();
  GT_MIN(0);
  if (blockIdx.x < 84) {
    const int cl = tid & 15, kg = tid >> 4;
    const int col = blockIdx.x * 32 + cl * 2;
    uint32_t v[14];
#pragma unroll
    for (int i = 0; i < 14; ++i) v[i] = *reinterpret_cast<const uint32_t*>(wm + (size_t)(kg * 14 + i) * (6 * DM) + col);
    float a0 = 0.f, a1 = 0.f;
#pragma unroll
    for (int i = 0; i < 14; ++i) {
      float cv = __bfloat162float(c[kg * 14 + i]);
      float sv = rbf(cv / (1.f + __expf(-cv)));
      a0 = fmaf(sv, bf_lo(v[i]), a0); a1 = fmaf(sv, bf_hi(v[i]), a1);
    }
    red[kg][cl * 2] = a0; red[kg][cl * 2 + 1] = a1;
    __syncthreads();
    if (tid < 32) {
      float s = 0.f;
#pragma unroll
      for (int i = 0; i < 32; ++i) s += red[i][tid];
      g_mod[blockIdx.x * 32 + tid] = rbf(s);
    }
  }
  if (blockIdx.x < 84) GT_MAX(1); else GT_MAX(13);
}

__device__ __forceinline__ void ln_row(const float (&x)[14], const float* __restrict__ shift, const float* __restrict__ scale,
                                       __nv_bfloat16* __restrict__ out, int lane) {
  float2 sc[7], sh[7];
#pragma unroll
  for (int i = 0; i < 7; ++i) {
    sc[i] = *reinterpret_cast<const float2*>(scale + i * 64 + lane * 2);
    sh[i] = *reinterpret_cast<const float2*>(shift + i * 64 + lane * 2);
  }
  float s = 0.f;
#pragma unroll
  for (int i = 0; i < 14; ++i) s += x[i];
#pragma unroll
  for (int o = 16; o; o >>= 1) s += __shfl_xor_sync(0xffffffffu, s, o);
  const float mean = s * (1.f / DM);
  float q = 0.f;
#pragma unroll
  for (int i = 0; i < 14; ++i) { float d = x[i] - mean; q = fmaf(d, d, q); }
#pragma unroll
  for (int o = 16; o; o >>= 1) q += __shfl_xor_sync(0xffffffffu, q, o);
  const float mb = rbf(mean), vb = rbf(q * (1.f / DM));
  const float den = rbf(sqrtf(rbf(vb + 1e-5f)));
#pragma unroll
  for (int i = 0; i < 7; ++i) {
    int col = i * 64 + lane * 2;
    float y0 = rbf(rbf(x[2 * i] - mb) / den), y1 = rbf(rbf(x[2 * i + 1] - mb) / den);
    y0 = rbf(y0 * rbf(1.f + sc[i].x)); y1 = rbf(y1 * rbf(1.f + sc[i].y));
    *reinterpret_cast<uint32_t*>(out + col) = pack_bf16(y0 + sh[i].x, y1 + sh[i].y);
  }
}

__global__ void __launch_bounds__(256) ln1_kernel(const __nv_bfloat16* __restrict__ x) {
  const int lane = threadIdx.x & 31, row = blockIdx.x * 8 + (threadIdx.x >> 5);
  float v[14];
#pragma unroll
  for (int i = 0; i < 7; ++i) {
    uint32_t u = *reinterpret_cast<const uint32_t*>(x + (size_t)row * DM + i * 64 + lane * 2);
    v[2 * i] = bf_lo(u); v[2 * i + 1] = bf_hi(u);
  }
  {
    float4 z = make_float4(0.f, 0.f, 0.f, 0.f);
    const int base = blockIdx.x * (8 * DM / 4);
    for (int i = threadIdx.x; i < 8 * DM / 4; i += 256) {
      reinterpret_cast<float4*>(g_acc1)[base + i] = z; reinterpret_cast<float4*>(g_acc2)[base + i] = z;
    }
  }
  pdl_wait();
  GT_MIN(2);
  ln_row(v, g_mod + 0 * DM, g_mod + 1 * DM, g_h + (size_t)row * DM, lane);
  GT_MAX(3);
  pdl_launch();
}

__global__ void __launch_bounds__(256) ln2_kernel(const __nv_bfloat16* __restrict__ x) {
  const int lane = threadIdx.x & 31, row = blockIdx.x * 8 + (threadIdx.x >> 5);
  float v[14];
  uint32_t xu[7];
#pragma unroll
  for (int i = 0; i < 7; ++i) xu[i] = *reinterpret_cast<const uint32_t*>(x + (size_t)row * DM + i * 64 + lane * 2);
  pdl_wait();
  GT_MIN(6);
  float2 av[7], gv[7];
#pragma unroll
  for (int i = 0; i < 7; ++i) {
    av[i] = *reinterpret_cast<const float2*>(g_acc1 + (size_t)row * DM + i * 64 + lane * 2);
    gv[i] = *reinterpret_cast<const float2*>(g_mod + 2 * DM + i * 64 + lane * 2);
  }
#pragma unroll
  for (int i = 0; i < 7; ++i) {
    int col = i * 64 + lane * 2;
    uint32_t u = xu[i];
    float t0 = rbf(gv[i].x * rbf(av[i].x)), t1 = rbf(gv[i].y * rbf(av[i].y));
    v[2 * i] = rbf(bf_lo(u) + t0); v[2 * i + 1] = rbf(bf_hi(u) + t1);
    *reinterpret_cast<uint32_t*>(g_x1 + (size_t)row * DM + col) = pack_bf16(v[2 * i], v[2 * i + 1]);
  }
  ln_row(v, g_mod + 3 * DM, g_mod + 4 * DM, g_h2 + (size_t)row * DM, lane);
  GT_MAX(7);
  pdl_launch();
}

__global__ void __launch_bounds__(256) final_kernel(__nv_bfloat16* __restrict__ out) {
  const int i = blockIdx.x * 256 + threadIdx.x;
  const int col = (i * 4) % DM;
  pdl_wait();
  GT_MIN(10);
  float4 a = reinterpret_cast<const float4*>(g_acc2)[i];
  uint2 u = reinterpret_cast<const uint2*>(g_x1)[i];
  float4 gb = *reinterpret_cast<const float4*>(g_mod + 5 * DM + col);
  uint2 o;
  o.x = pack_bf16(bf_lo(u.x) + rbf(gb.x * rbf(a.x)), bf_hi(u.x) + rbf(gb.y * rbf(a.y)));
  o.y = pack_bf16(bf_lo(u.y) + rbf(gb.z * rbf(a.z)), bf_hi(u.y) + rbf(gb.w * rbf(a.w)));
  reinterpret_cast<uint2*>(out)[i] = o;
  GT_MAX(11);
}

typedef CUresult (*EncodeFn)(CUtensorMap*, CUtensorMapDataType, cuuint32_t, void*, const cuuint64_t*, const cuuint64_t*,
                             const cuuint32_t*, const cuuint32_t*, CUtensorMapInterleave, CUtensorMapSwizzle,
                             CUtensorMapL2promotion, CUtensorMapFloatOOBfill);

static CUtensorMap make_map(EncodeFn enc, const void* ptr, uint64_t cols, uint64_t rows, uint32_t bx, uint32_t by,
                            bool f32 = false) {
  CUtensorMap m;
  cuuint64_t dims[2] = {cols, rows};
  cuuint64_t strides[1] = {cols * (f32 ? 4 : 2)};
  cuuint32_t box[2] = {bx, by};
  cuuint32_t es[2] = {1, 1};
  enc(&m, f32 ? CU_TENSOR_MAP_DATA_TYPE_FLOAT32 : CU_TENSOR_MAP_DATA_TYPE_BFLOAT16, 2, const_cast<void*>(ptr), dims, strides, box, es, CU_TENSOR_MAP_INTERLEAVE_NONE,
      CU_TENSOR_MAP_SWIZZLE_128B, CU_TENSOR_MAP_L2_PROMOTION_L2_256B, CU_TENSOR_MAP_FLOAT_OOB_FILL_NONE);
  return m;
}

template <typename... Args>
static void launch(void (*k)(Args...), dim3 grid, dim3 block, size_t smem, bool pdl, Args... args) {
  cudaLaunchConfig_t cfg = {};
  cfg.gridDim = grid; cfg.blockDim = block; cfg.dynamicSmemBytes = smem; cfg.stream = cudaStreamPerThread;
  cudaLaunchAttribute at[1];
  at[0].id = cudaLaunchAttributeProgrammaticStreamSerialization; at[0].val.programmaticStreamSerializationAllowed = 1;
  cfg.attrs = at; cfg.numAttrs = pdl ? 1 : 0;
  cudaLaunchKernelEx(&cfg, k, args...);
}

extern "C" void kernel_launch(void* const* d_in, const int* in_sizes, int n_in, void* d_out, int out_size) {
  const __nv_bfloat16* x = (const __nv_bfloat16*)d_in[0];
  const void* kc = d_in[1]; const void* vc = d_in[2]; const void* wq = d_in[3]; const void* wo = d_in[4];
  const void* w1 = d_in[6]; const void* w2 = d_in[7];
  const __nv_bfloat16* c = (const __nv_bfloat16*)d_in[8];
  const __nv_bfloat16* wm = (const __nv_bfloat16*)d_in[9];

  void* fn = nullptr; cudaDriverEntryPointQueryResult qr;
  cudaGetDriverEntryPoint("cuTensorMapEncodeTiled", &fn, cudaEnableDefault, &qr);
  EncodeFn enc = (EncodeFn)fn;
  void *p_h, *p_oA, *p_h2, *p_a1, *p_a2;
  cudaGetSymbolAddress(&p_a1, g_acc1); cudaGetSymbolAddress(&p_a2, g_acc2);
  cudaGetSymbolAddress(&p_h, g_h); cudaGetSymbolAddress(&p_oA, g_oA); cudaGetSymbolAddress(&p_h2, g_h2);
  CUtensorMap tm_h = make_map(enc, p_h, DM, SEQ, 64, 128);
  CUtensorMap tm_wq = make_map(enc, wq, 4096, DM, 64, 64);
  CUtensorMap tm_k = make_map(enc, kc, DH, HKV * SKV, 64, 128);
  CUtensorMap tm_v = make_map(enc, vc, DH, HKV * SKV, 64, 64);
  CUtensorMap tm_wo = make_map(enc, wo, DM, 4096, 64, 64);
  CUtensorMap tm_oA = make_map(enc, p_oA, DH, HKV * SEQ, 64, 128);
  CUtensorMap tm_oAs = make_map(enc, p_oA, DH, HKV * SEQ, 64, 64);
  CUtensorMap tm_a1 = make_map(enc, p_a1, DM, SEQ, 32, 8, true), tm_a2 = make_map(enc, p_a2, DM, SEQ, 32, 8, true);
  CUtensorMap tm_h2 = make_map(enc, p_h2, DM, SEQ, 64, 64);
  CUtensorMap tm_w1 = make_map(enc, w1, DFF, DM, 64, 64);
  CUtensorMap tm_w2 = make_map(enc, w2, DM, DFF, 64, 64);
  cudaFuncSetAttribute(attn_kernel, cudaFuncAttributeMaxDynamicSharedMemorySize, SM_TOTAL);
  cudaFuncSetAttribute(ffn_kernel, cudaFuncAttributeMaxDynamicSharedMemorySize, F_TOTAL);

  launch(mod_kernel, dim3(84), dim3(512), 0, false, c, wm);
  launch(ln1_kernel, dim3(SEQ / 8), dim3(256), 0, true, x);
  launch(attn_kernel, dim3(16, 8), dim3(384), SM_TOTAL, true, tm_h, tm_wq, tm_k, tm_v, tm_wo, tm_oA, tm_oAs, tm_a1);
  launch(ln2_kernel, dim3(SEQ / 8), dim3(256), 0, true, x);
  launch(ffn_kernel, dim3(32, 4), dim3(384), F_TOTAL, true, tm_h2, tm_w1, tm_w2, tm_a2);
  launch(final_kernel, dim3(SEQ * DM / 1024), dim3(256), 0, true, (__nv_bfloat16*)d_out);
}
```
